```python
import torch

def _softmax(x, axis=-1):
    return torch.softmax(x, dim=axis)
def _gelu(x):
    return torch.nn.functional.gelu(x, approximate="tanh")
def _silu(x):
    return torch.nn.functional.silu(x)
def _sigmoid(x):
    return torch.sigmoid(x)
def _layernorm(x, axis=-1, eps=1e-5):
    m = x.mean(dim=axis, keepdim=True)
    v = x.var(dim=axis, keepdim=True, unbiased=False)
    return (x - m) / torch.sqrt(v + eps)
def _scatter_add(tgt, idx, src, axis=0):
    return tgt.clone().index_add_(axis, idx, src)
def _segment_sum(src, seg, n):
    out = torch.zeros((n,) + src.shape[1:], dtype=src.dtype)
    return out.index_add_(0, seg, src)
def _pad(x, pw):
    flat = tuple(v for pair in reversed(pw) for v in pair)
    return torch.nn.functional.pad(x, flat)

kernel_name = 'concat_heads__grouped_kv_mqa__spectral_gfnet__prompt'

def setup_inputs():

    _w = (lambda a: (lambda t: t.to(torch.bfloat16) if t.is_floating_point() else t)(torch.as_tensor(a)))
    def _A_setup():
        B, S, D, H = 1, 2048, 448, 16
        Dh = D // H
        return {
            "x": _w((lambda *s: torch.randn(*s, dtype=torch.bfloat16) * 0.05)(B, S, D)),
            "wq": _w((lambda *s: torch.randn(*s, dtype=torch.bfloat16) * 0.8)(D, H * Dh)),
            "wk": _w((lambda *s: torch.randn(*s, dtype=torch.bfloat16) * 0.8)(D, Dh)),
            "wv": _w((lambda *s: torch.randn(*s, dtype=torch.bfloat16) * 0.05)(D, Dh)),
            "wo": _w((lambda *s: torch.randn(*s, dtype=torch.bfloat16) * 0.05)(H * Dh, D)),
        }
    _A_in = _A_setup()

    def _B_setup():
        B, S, D = 1, 2048, 448
        Df = D // 2 + 1
        return {
            "x": _w((lambda *s: torch.randn(*s, dtype=torch.bfloat16) * 0.05)(B, S, D)),
            "w_r": _w((lambda *s: torch.randn(*s, dtype=torch.bfloat16) * 0.4)(S, Df) * 0.02),
            "w_i": _w((lambda *s: torch.randn(*s, dtype=torch.bfloat16) * 0.4)(S, Df) * 0.02),
        }
    _B_in = _B_setup()

    return {
        "A_x": _A_in["x"],
        "A_wq": _A_in["wq"],
        "A_wk": _A_in["wk"],
        "A_wv": _A_in["wv"],
        "A_wo": _A_in["wo"],
        "B_x": _B_in["x"],
        "B_w_r": _B_in["w_r"],
        "B_w_i": _B_in["w_i"],
    }

def reference(A_x, A_wq, A_wk, A_wv, A_wo, B_x, B_w_r, B_w_i):
    def _A_ref(x, wq, wk, wv, wo):
        B, S, D = x.shape
        H = 16
        Dh = D // H
        q = (lambda x, *d: x.permute(*d))((x @ wq).reshape(B, S, H, Dh), 0, 2, 1, 3)
        k = x @ wk
        v = x @ wv
        scores = torch.einsum("bhqd,bkd->bhqk", q, k) * (Dh ** -0.5)
        p = _softmax(scores, axis=-1)
        o = torch.einsum("bhqk,bkd->bhqd", p, v)
        return (lambda x, *d: x.permute(*d))(o, 0, 2, 1, 3).reshape(B, S, H * Dh) @ wo

    def _B_ref(x, w_r, w_i):
        B, S, D = x.shape
        X = (lambda x, axes=(-2,-1): torch.fft.rfft2(x.float(), dim=axes))(x, axes=(-2, -1))
        W = w_r + 1j * w_i
        X = X * W
        y = (lambda x, s, axes=(-2,-1): torch.fft.irfft2(x, s=s, dim=axes).to(torch.bfloat16))(X, (S, D), axes=(-2, -1))
        return y

    a = _A_ref(A_x, A_wq, A_wk, A_wv, A_wo)
    b = _B_ref(B_x, B_w_r, B_w_i)
    return torch.concatenate([a, b], axis=-1)
```

```cpp
#include <cuda_runtime.h>
#include <cuda.h>
#include <cuda_bf16.h>
#include <stdint.h>

__device__ __align__(16) const float2 c_tw2048[2048] = {
{1.0f,-0.0f},{0.999995291f,-0.00306795677f},{0.999981165f,-0.00613588467f},{0.999957621f,-0.00920375437f},
{0.999924719f,-0.0122715384f},{0.99988234f,-0.015339206f},{0.999830604f,-0.0184067301f},{0.99976939f,-0.0214740802f},
{0.999698818f,-0.024541229f},{0.999618828f,-0.027608145f},{0.999529421f,-0.030674804f},{0.999430597f,-0.0337411724f},
{0.999322355f,-0.0368072242f},{0.999204755f,-0.0398729257f},{0.999077737f,-0.0429382585f},{0.998941302f,-0.0460031815f},
{0.99879545f,-0.0490676761f},{0.998640239f,-0.052131705f},{0.998475552f,-0.0551952459f},{0.998301566f,-0.0582582653f},
{0.998118103f,-0.061320737f},{0.997925282f,-0.0643826276f},{0.997723043f,-0.0674439222f},{0.997511446f,-0.070504576f},
{0.997290432f,-0.0735645667f},{0.997060061f,-0.0766238645f},{0.996820271f,-0.0796824396f},{0.996571124f,-0.0827402622f},
{0.996312618f,-0.0857973099f},{0.996044695f,-0.0888535529f},{0.995767415f,-0.0919089541f},{0.995480776f,-0.0949634984f},
{0.99518472f,-0.0980171412f},{0.994879305f,-0.10106986f},{0.994564593f,-0.104121633f},{0.994240463f,-0.107172422f},
{0.993906975f,-0.110222206f},{0.993564129f,-0.113270953f},{0.993211925f,-0.116318628f},{0.992850423f,-0.119365215f},
{0.992479563f,-0.122410677f},{0.992099285f,-0.125454977f},{0.991709769f,-0.128498107f},{0.991310835f,-0.13154003f},
{0.990902662f,-0.134580702f},{0.990485072f,-0.137620121f},{0.990058184f,-0.140658244f},{0.989621997f,-0.143695027f},
{0.989176512f,-0.146730468f},{0.988721669f,-0.149764538f},{0.988257587f,-0.152797192f},{0.987784147f,-0.155828401f},
{0.987301409f,-0.15885815f},{0.986809373f,-0.161886394f},{0.986308098f,-0.164913118f},{0.985797524f,-0.167938292f},
{0.985277653f,-0.170961887f},{0.984748483f,-0.173983872f},{0.984210074f,-0.177004218f},{0.983662426f,-0.180022895f},
{0.983105481f,-0.183039889f},{0.982539296f,-0.186055154f},{0.981963873f,-0.18906866f},{0.981379211f,-0.192080393f},
{0.980785251f,-0.195090324f},{0.980182111f,-0.198098406f},{0.979569793f,-0.201104641f},{0.978948176f,-0.204108968f},
{0.97831738f,-0.207111374f},{0.977677345f,-0.210111842f},{0.977028131f,-0.213110313f},{0.976369739f,-0.216106802f},
{0.975702107f,-0.219101235f},{0.975025356f,-0.222093627f},{0.974339366f,-0.225083917f},{0.973644257f,-0.228072077f},
{0.972939968f,-0.231058106f},{0.972226501f,-0.234041959f},{0.971503913f,-0.237023607f},{0.970772147f,-0.24000302f},
{0.970031261f,-0.242980182f},{0.969281256f,-0.24595505f},{0.968522072f,-0.248927608f},{0.967753828f,-0.251897812f},
{0.966976464f,-0.254865646f},{0.966189981f,-0.257831097f},{0.965394437f,-0.260794103f},{0.964589775f,-0.263754666f},
{0.963776052f,-0.266712755f},{0.962953269f,-0.269668311f},{0.962121427f,-0.272621363f},{0.961280465f,-0.275571823f},
{0.960430503f,-0.27851969f},{0.95957154f,-0.281464934f},{0.958703458f,-0.284407526f},{0.957826436f,-0.287347466f},
{0.956940353f,-0.290284663f},{0.95604527f,-0.293219149f},{0.955141187f,-0.296150893f},{0.954228103f,-0.299079835f},
{0.953306019f,-0.302005947f},{0.952374995f,-0.304929227f},{0.95143503f,-0.307849646f},{0.950486064f,-0.310767144f},
{0.949528158f,-0.313681751f},{0.94856137f,-0.316593379f},{0.947585583f,-0.319502026f},{0.946600914f,-0.322407693f},
{0.945607305f,-0.32531029f},{0.944604814f,-0.328209847f},{0.943593442f,-0.331106305f},{0.94257319f,-0.333999664f},
{0.941544056f,-0.336889863f},{0.940506041f,-0.339776874f},{0.939459205f,-0.342660725f},{0.938403547f,-0.345541328f},
{0.937339008f,-0.348418683f},{0.936265647f,-0.351292759f},{0.935183525f,-0.354163527f},{0.934092522f,-0.357030958f},
{0.932992816f,-0.359895051f},{0.931884289f,-0.362755716f},{0.93076694f,-0.365612984f},{0.929640889f,-0.368466824f},
{0.928506076f,-0.371317208f},{0.927362502f,-0.374164075f},{0.926210225f,-0.377007425f},{0.925049245f,-0.379847199f},
{0.923879504f,-0.382683426f},{0.92270112f,-0.385516047f},{0.921514034f,-0.388345033f},{0.920318305f,-0.391170382f},
{0.919113874f,-0.393992037f},{0.917900801f,-0.396809995f},{0.916679084f,-0.399624199f},{0.915448725f,-0.402434647f},
{0.914209783f,-0.405241311f},{0.912962198f,-0.408044159f},{0.91170603f,-0.410843164f},{0.910441279f,-0.413638324f},
{0.909168005f,-0.416429549f},{0.907886088f,-0.419216901f},{0.906595707f,-0.422000259f},{0.905296743f,-0.424779683f},
{0.903989315f,-0.427555084f},{0.902673304f,-0.430326492f},{0.901348829f,-0.433093816f},{0.900015891f,-0.435857087f},
{0.898674488f,-0.438616246f},{0.897324562f,-0.441371262f},{0.895966232f,-0.444122136f},{0.894599497f,-0.446868837f},
{0.893224299f,-0.449611336f},{0.891840696f,-0.452349573f},{0.890448749f,-0.455083579f},{0.889048338f,-0.457813293f},
{0.887639642f,-0.460538715f},{0.886222541f,-0.463259786f},{0.884797096f,-0.465976506f},{0.883363366f,-0.468688816f},
{0.881921291f,-0.471396744f},{0.880470872f,-0.474100202f},{0.879012227f,-0.47679922f},{0.877545297f,-0.479493767f},
{0.876070082f,-0.482183784f},{0.874586642f,-0.484869242f},{0.873094976f,-0.487550169f},{0.871595085f,-0.490226477f},
{0.870086968f,-0.492898196f},{0.868570685f,-0.495565265f},{0.867046237f,-0.498227656f},{0.865513623f,-0.500885367f},
{0.863972843f,-0.50353837f},{0.862423956f,-0.506186664f},{0.860866964f,-0.50883013f},{0.859301805f,-0.511468828f},
{0.857728601f,-0.514102757f},{0.856147349f,-0.516731799f},{0.854557991f,-0.519356012f},{0.852960587f,-0.521975279f},
{0.851355195f,-0.524589658f},{0.849741757f,-0.527199149f},{0.848120332f,-0.529803634f},{0.84649092f,-0.532403111f},
{0.84485358f,-0.534997642f},{0.843208253f,-0.537587047f},{0.841554999f,-0.540171444f},{0.839893818f,-0.542750776f},
{0.838224709f,-0.545324981f},{0.836547732f,-0.547894061f},{0.834862888f,-0.550457954f},{0.833170176f,-0.553016722f},
{0.831469595f,-0.555570245f},{0.829761207f,-0.558118522f},{0.82804507f,-0.560661554f},{0.826321065f,-0.563199341f},
{0.824589312f,-0.565731823f},{0.82284981f,-0.568258941f},{0.8211025f,-0.570780754f},{0.819347501f,-0.573297143f},
{0.817584813f,-0.575808167f},{0.815814435f,-0.578313768f},{0.81403631f,-0.580813944f},{0.812250614f,-0.583308637f},
{0.81045717f,-0.585797846f},{0.808656156f,-0.588281572f},{0.806847572f,-0.590759695f},{0.805031359f,-0.593232274f},
{0.803207517f,-0.59569931f},{0.801376164f,-0.598160684f},{0.799537241f,-0.600616455f},{0.797690868f,-0.603066623f},
{0.795836926f,-0.605511069f},{0.793975472f,-0.607949793f},{0.792106569f,-0.610382795f},{0.790230215f,-0.612810075f},
{0.78834641f,-0.615231574f},{0.786455214f,-0.61764729f},{0.784556568f,-0.620057225f},{0.78265059f,-0.622461259f},
{0.780737221f,-0.624859512f},{0.778816521f,-0.627251804f},{0.77688849f,-0.629638255f},{0.774953127f,-0.632018745f},
{0.773010433f,-0.634393275f},{0.771060526f,-0.636761844f},{0.769103348f,-0.639124453f},{0.767138898f,-0.641481042f},
{0.765167236f,-0.643831551f},{0.763188422f,-0.64617604f},{0.761202395f,-0.64851439f},{0.759209216f,-0.65084666f},
{0.757208824f,-0.653172851f},{0.755201399f,-0.655492842f},{0.753186822f,-0.657806695f},{0.751165152f,-0.660114348f},
{0.749136388f,-0.662415802f},{0.747100592f,-0.664710999f},{0.745057762f,-0.666999936f},{0.743007958f,-0.669282615f},
{0.740951121f,-0.671558976f},{0.73888731f,-0.673829019f},{0.736816585f,-0.676092684f},{0.734738886f,-0.678350031f},
{0.732654274f,-0.680601001f},{0.730562747f,-0.682845533f},{0.728464365f,-0.685083687f},{0.726359129f,-0.687315345f},
{0.724247098f,-0.689540565f},{0.722128212f,-0.691759229f},{0.720002532f,-0.693971455f},{0.717870057f,-0.696177125f},
{0.715730846f,-0.698376238f},{0.71358484f,-0.700568795f},{0.711432219f,-0.702754736f},{0.709272802f,-0.704934061f},
{0.707106769f,-0.707106769f},{0.704934061f,-0.709272802f},{0.702754736f,-0.711432219f},{0.700568795f,-0.71358484f},
{0.698376238f,-0.715730846f},{0.696177125f,-0.717870057f},{0.693971455f,-0.720002532f},{0.691759229f,-0.722128212f},
{0.689540565f,-0.724247098f},{0.687315345f,-0.726359129f},{0.685083687f,-0.728464365f},{0.682845533f,-0.730562747f},
{0.680601001f,-0.732654274f},{0.678350031f,-0.734738886f},{0.676092684f,-0.736816585f},{0.673829019f,-0.73888731f},
{0.671558976f,-0.740951121f},{0.669282615f,-0.743007958f},{0.666999936f,-0.745057762f},{0.664710999f,-0.747100592f},
{0.662415802f,-0.749136388f},{0.660114348f,-0.751165152f},{0.657806695f,-0.753186822f},{0.655492842f,-0.755201399f},
{0.653172851f,-0.757208824f},{0.65084666f,-0.759209216f},{0.64851439f,-0.761202395f},{0.64617604f,-0.763188422f},
{0.643831551f,-0.765167236f},{0.641481042f,-0.767138898f},{0.639124453f,-0.769103348f},{0.636761844f,-0.771060526f},
{0.634393275f,-0.773010433f},{0.632018745f,-0.774953127f},{0.629638255f,-0.77688849f},{0.627251804f,-0.778816521f},
{0.624859512f,-0.780737221f},{0.622461259f,-0.78265059f},{0.620057225f,-0.784556568f},{0.61764729f,-0.786455214f},
{0.615231574f,-0.78834641f},{0.612810075f,-0.790230215f},{0.610382795f,-0.792106569f},{0.607949793f,-0.793975472f},
{0.605511069f,-0.795836926f},{0.603066623f,-0.797690868f},{0.600616455f,-0.799537241f},{0.598160684f,-0.801376164f},
{0.59569931f,-0.803207517f},{0.593232274f,-0.805031359f},{0.590759695f,-0.806847572f},{0.588281572f,-0.808656156f},
{0.585797846f,-0.81045717f},{0.583308637f,-0.812250614f},{0.580813944f,-0.81403631f},{0.578313768f,-0.815814435f},
{0.575808167f,-0.817584813f},{0.573297143f,-0.819347501f},{0.570780754f,-0.8211025f},{0.568258941f,-0.82284981f},
{0.565731823f,-0.824589312f},{0.563199341f,-0.826321065f},{0.560661554f,-0.82804507f},{0.558118522f,-0.829761207f},
{0.555570245f,-0.831469595f},{0.553016722f,-0.833170176f},{0.550457954f,-0.834862888f},{0.547894061f,-0.836547732f},
{0.545324981f,-0.838224709f},{0.542750776f,-0.839893818f},{0.540171444f,-0.841554999f},{0.537587047f,-0.843208253f},
{0.534997642f,-0.84485358f},{0.532403111f,-0.84649092f},{0.529803634f,-0.848120332f},{0.527199149f,-0.849741757f},
{0.524589658f,-0.851355195f},{0.521975279f,-0.852960587f},{0.519356012f,-0.854557991f},{0.516731799f,-0.856147349f},
{0.514102757f,-0.857728601f},{0.511468828f,-0.859301805f},{0.50883013f,-0.860866964f},{0.506186664f,-0.862423956f},
{0.50353837f,-0.863972843f},{0.500885367f,-0.865513623f},{0.498227656f,-0.867046237f},{0.495565265f,-0.868570685f},
{0.492898196f,-0.870086968f},{0.490226477f,-0.871595085f},{0.487550169f,-0.873094976f},{0.484869242f,-0.874586642f},
{0.482183784f,-0.876070082f},{0.479493767f,-0.877545297f},{0.47679922f,-0.879012227f},{0.474100202f,-0.880470872f},
{0.471396744f,-0.881921291f},{0.468688816f,-0.883363366f},{0.465976506f,-0.884797096f},{0.463259786f,-0.886222541f},
{0.460538715f,-0.887639642f},{0.457813293f,-0.889048338f},{0.455083579f,-0.890448749f},{0.452349573f,-0.891840696f},
{0.449611336f,-0.893224299f},{0.446868837f,-0.894599497f},{0.444122136f,-0.895966232f},{0.441371262f,-0.897324562f},
{0.438616246f,-0.898674488f},{0.435857087f,-0.900015891f},{0.433093816f,-0.901348829f},{0.430326492f,-0.902673304f},
{0.427555084f,-0.903989315f},{0.424779683f,-0.905296743f},{0.422000259f,-0.906595707f},{0.419216901f,-0.907886088f},
{0.416429549f,-0.909168005f},{0.413638324f,-0.910441279f},{0.410843164f,-0.91170603f},{0.408044159f,-0.912962198f},
{0.405241311f,-0.914209783f},{0.402434647f,-0.915448725f},{0.399624199f,-0.916679084f},{0.396809995f,-0.917900801f},
{0.393992037f,-0.919113874f},{0.391170382f,-0.920318305f},{0.388345033f,-0.921514034f},{0.385516047f,-0.92270112f},
{0.382683426f,-0.923879504f},{0.379847199f,-0.925049245f},{0.377007425f,-0.926210225f},{0.374164075f,-0.927362502f},
{0.371317208f,-0.928506076f},{0.368466824f,-0.929640889f},{0.365612984f,-0.93076694f},{0.362755716f,-0.931884289f},
{0.359895051f,-0.932992816f},{0.357030958f,-0.934092522f},{0.354163527f,-0.935183525f},{0.351292759f,-0.936265647f},
{0.348418683f,-0.937339008f},{0.345541328f,-0.938403547f},{0.342660725f,-0.939459205f},{0.339776874f,-0.940506041f},
{0.336889863f,-0.941544056f},{0.333999664f,-0.94257319f},{0.331106305f,-0.943593442f},{0.328209847f,-0.944604814f},
{0.32531029f,-0.945607305f},{0.322407693f,-0.946600914f},{0.319502026f,-0.947585583f},{0.316593379f,-0.94856137f},
{0.313681751f,-0.949528158f},{0.310767144f,-0.950486064f},{0.307849646f,-0.95143503f},{0.304929227f,-0.952374995f},
{0.302005947f,-0.953306019f},{0.299079835f,-0.954228103f},{0.296150893f,-0.955141187f},{0.293219149f,-0.95604527f},
{0.290284663f,-0.956940353f},{0.287347466f,-0.957826436f},{0.284407526f,-0.958703458f},{0.281464934f,-0.95957154f},
{0.27851969f,-0.960430503f},{0.275571823f,-0.961280465f},{0.272621363f,-0.962121427f},{0.269668311f,-0.962953269f},
{0.266712755f,-0.963776052f},{0.263754666f,-0.964589775f},{0.260794103f,-0.965394437f},{0.257831097f,-0.966189981f},
{0.254865646f,-0.966976464f},{0.251897812f,-0.967753828f},{0.248927608f,-0.968522072f},{0.24595505f,-0.969281256f},
{0.242980182f,-0.970031261f},{0.24000302f,-0.970772147f},{0.237023607f,-0.971503913f},{0.234041959f,-0.972226501f},
{0.231058106f,-0.972939968f},{0.228072077f,-0.973644257f},{0.225083917f,-0.974339366f},{0.222093627f,-0.975025356f},
{0.219101235f,-0.975702107f},{0.216106802f,-0.976369739f},{0.213110313f,-0.977028131f},{0.210111842f,-0.977677345f},
{0.207111374f,-0.97831738f},{0.204108968f,-0.978948176f},{0.201104641f,-0.979569793f},{0.198098406f,-0.980182111f},
{0.195090324f,-0.980785251f},{0.192080393f,-0.981379211f},{0.18906866f,-0.981963873f},{0.186055154f,-0.982539296f},
{0.183039889f,-0.983105481f},{0.180022895f,-0.983662426f},{0.177004218f,-0.984210074f},{0.173983872f,-0.984748483f},
{0.170961887f,-0.985277653f},{0.167938292f,-0.985797524f},{0.164913118f,-0.986308098f},{0.161886394f,-0.986809373f},
{0.15885815f,-0.987301409f},{0.155828401f,-0.987784147f},{0.152797192f,-0.988257587f},{0.149764538f,-0.988721669f},
{0.146730468f,-0.989176512f},{0.143695027f,-0.989621997f},{0.140658244f,-0.990058184f},{0.137620121f,-0.990485072f},
{0.134580702f,-0.990902662f},{0.13154003f,-0.991310835f},{0.128498107f,-0.991709769f},{0.125454977f,-0.992099285f},
{0.122410677f,-0.992479563f},{0.119365215f,-0.992850423f},{0.116318628f,-0.993211925f},{0.113270953f,-0.993564129f},
{0.110222206f,-0.993906975f},{0.107172422f,-0.994240463f},{0.104121633f,-0.994564593f},{0.10106986f,-0.994879305f},
{0.0980171412f,-0.99518472f},{0.0949634984f,-0.995480776f},{0.0919089541f,-0.995767415f},{0.0888535529f,-0.996044695f},
{0.0857973099f,-0.996312618f},{0.0827402622f,-0.996571124f},{0.0796824396f,-0.996820271f},{0.0766238645f,-0.997060061f},
{0.0735645667f,-0.997290432f},{0.070504576f,-0.997511446f},{0.0674439222f,-0.997723043f},{0.0643826276f,-0.997925282f},
{0.061320737f,-0.998118103f},{0.0582582653f,-0.998301566f},{0.0551952459f,-0.998475552f},{0.052131705f,-0.998640239f},
{0.0490676761f,-0.99879545f},{0.0460031815f,-0.998941302f},{0.0429382585f,-0.999077737f},{0.0398729257f,-0.999204755f},
{0.0368072242f,-0.999322355f},{0.0337411724f,-0.999430597f},{0.030674804f,-0.999529421f},{0.027608145f,-0.999618828f},
{0.024541229f,-0.999698818f},{0.0214740802f,-0.99976939f},{0.0184067301f,-0.999830604f},{0.015339206f,-0.99988234f},
{0.0122715384f,-0.999924719f},{0.00920375437f,-0.999957621f},{0.00613588467f,-0.999981165f},{0.00306795677f,-0.999995291f},
{6.12323426e-17f,-1.0f},{-0.00306795677f,-0.999995291f},{-0.00613588467f,-0.999981165f},{-0.00920375437f,-0.999957621f},
{-0.0122715384f,-0.999924719f},{-0.015339206f,-0.99988234f},{-0.0184067301f,-0.999830604f},{-0.0214740802f,-0.99976939f},
{-0.024541229f,-0.999698818f},{-0.027608145f,-0.999618828f},{-0.030674804f,-0.999529421f},{-0.0337411724f,-0.999430597f},
{-0.0368072242f,-0.999322355f},{-0.0398729257f,-0.999204755f},{-0.0429382585f,-0.999077737f},{-0.0460031815f,-0.998941302f},
{-0.0490676761f,-0.99879545f},{-0.052131705f,-0.998640239f},{-0.0551952459f,-0.998475552f},{-0.0582582653f,-0.998301566f},
{-0.061320737f,-0.998118103f},{-0.0643826276f,-0.997925282f},{-0.0674439222f,-0.997723043f},{-0.070504576f,-0.997511446f},
{-0.0735645667f,-0.997290432f},{-0.0766238645f,-0.997060061f},{-0.0796824396f,-0.996820271f},{-0.0827402622f,-0.996571124f},
{-0.0857973099f,-0.996312618f},{-0.0888535529f,-0.996044695f},{-0.0919089541f,-0.995767415f},{-0.0949634984f,-0.995480776f},
{-0.0980171412f,-0.99518472f},{-0.10106986f,-0.994879305f},{-0.104121633f,-0.994564593f},{-0.107172422f,-0.994240463f},
{-0.110222206f,-0.993906975f},{-0.113270953f,-0.993564129f},{-0.116318628f,-0.993211925f},{-0.119365215f,-0.992850423f},
{-0.122410677f,-0.992479563f},{-0.125454977f,-0.992099285f},{-0.128498107f,-0.991709769f},{-0.13154003f,-0.991310835f},
{-0.134580702f,-0.990902662f},{-0.137620121f,-0.990485072f},{-0.140658244f,-0.990058184f},{-0.143695027f,-0.989621997f},
{-0.146730468f,-0.989176512f},{-0.149764538f,-0.988721669f},{-0.152797192f,-0.988257587f},{-0.155828401f,-0.987784147f},
{-0.15885815f,-0.987301409f},{-0.161886394f,-0.986809373f},{-0.164913118f,-0.986308098f},{-0.167938292f,-0.985797524f},
{-0.170961887f,-0.985277653f},{-0.173983872f,-0.984748483f},{-0.177004218f,-0.984210074f},{-0.180022895f,-0.983662426f},
{-0.183039889f,-0.983105481f},{-0.186055154f,-0.982539296f},{-0.18906866f,-0.981963873f},{-0.192080393f,-0.981379211f},
{-0.195090324f,-0.980785251f},{-0.198098406f,-0.980182111f},{-0.201104641f,-0.979569793f},{-0.204108968f,-0.978948176f},
{-0.207111374f,-0.97831738f},{-0.210111842f,-0.977677345f},{-0.213110313f,-0.977028131f},{-0.216106802f,-0.976369739f},
{-0.219101235f,-0.975702107f},{-0.222093627f,-0.975025356f},{-0.225083917f,-0.974339366f},{-0.228072077f,-0.973644257f},
{-0.231058106f,-0.972939968f},{-0.234041959f,-0.972226501f},{-0.237023607f,-0.971503913f},{-0.24000302f,-0.970772147f},
{-0.242980182f,-0.970031261f},{-0.24595505f,-0.969281256f},{-0.248927608f,-0.968522072f},{-0.251897812f,-0.967753828f},
{-0.254865646f,-0.966976464f},{-0.257831097f,-0.966189981f},{-0.260794103f,-0.965394437f},{-0.263754666f,-0.964589775f},
{-0.266712755f,-0.963776052f},{-0.269668311f,-0.962953269f},{-0.272621363f,-0.962121427f},{-0.275571823f,-0.961280465f},
{-0.27851969f,-0.960430503f},{-0.281464934f,-0.95957154f},{-0.284407526f,-0.958703458f},{-0.287347466f,-0.957826436f},
{-0.290284663f,-0.956940353f},{-0.293219149f,-0.95604527f},{-0.296150893f,-0.955141187f},{-0.299079835f,-0.954228103f},
{-0.302005947f,-0.953306019f},{-0.304929227f,-0.952374995f},{-0.307849646f,-0.95143503f},{-0.310767144f,-0.950486064f},
{-0.313681751f,-0.949528158f},{-0.316593379f,-0.94856137f},{-0.319502026f,-0.947585583f},{-0.322407693f,-0.946600914f},
{-0.32531029f,-0.945607305f},{-0.328209847f,-0.944604814f},{-0.331106305f,-0.943593442f},{-0.333999664f,-0.94257319f},
{-0.336889863f,-0.941544056f},{-0.339776874f,-0.940506041f},{-0.342660725f,-0.939459205f},{-0.345541328f,-0.938403547f},
{-0.348418683f,-0.937339008f},{-0.351292759f,-0.936265647f},{-0.354163527f,-0.935183525f},{-0.357030958f,-0.934092522f},
{-0.359895051f,-0.932992816f},{-0.362755716f,-0.931884289f},{-0.365612984f,-0.93076694f},{-0.368466824f,-0.929640889f},
{-0.371317208f,-0.928506076f},{-0.374164075f,-0.927362502f},{-0.377007425f,-0.926210225f},{-0.379847199f,-0.925049245f},
{-0.382683426f,-0.923879504f},{-0.385516047f,-0.92270112f},{-0.388345033f,-0.921514034f},{-0.391170382f,-0.920318305f},
{-0.393992037f,-0.919113874f},{-0.396809995f,-0.917900801f},{-0.399624199f,-0.916679084f},{-0.402434647f,-0.915448725f},
{-0.405241311f,-0.914209783f},{-0.408044159f,-0.912962198f},{-0.410843164f,-0.91170603f},{-0.413638324f,-0.910441279f},
{-0.416429549f,-0.909168005f},{-0.419216901f,-0.907886088f},{-0.422000259f,-0.906595707f},{-0.424779683f,-0.905296743f},
{-0.427555084f,-0.903989315f},{-0.430326492f,-0.902673304f},{-0.433093816f,-0.901348829f},{-0.435857087f,-0.900015891f},
{-0.438616246f,-0.898674488f},{-0.441371262f,-0.897324562f},{-0.444122136f,-0.895966232f},{-0.446868837f,-0.894599497f},
{-0.449611336f,-0.893224299f},{-0.452349573f,-0.891840696f},{-0.455083579f,-0.890448749f},{-0.457813293f,-0.889048338f},
{-0.460538715f,-0.887639642f},{-0.463259786f,-0.886222541f},{-0.465976506f,-0.884797096f},{-0.468688816f,-0.883363366f},
{-0.471396744f,-0.881921291f},{-0.474100202f,-0.880470872f},{-0.47679922f,-0.879012227f},{-0.479493767f,-0.877545297f},
{-0.482183784f,-0.876070082f},{-0.484869242f,-0.874586642f},{-0.487550169f,-0.873094976f},{-0.490226477f,-0.871595085f},
{-0.492898196f,-0.870086968f},{-0.495565265f,-0.868570685f},{-0.498227656f,-0.867046237f},{-0.500885367f,-0.865513623f},
{-0.50353837f,-0.863972843f},{-0.506186664f,-0.862423956f},{-0.50883013f,-0.860866964f},{-0.511468828f,-0.859301805f},
{-0.514102757f,-0.857728601f},{-0.516731799f,-0.856147349f},{-0.519356012f,-0.854557991f},{-0.521975279f,-0.852960587f},
{-0.524589658f,-0.851355195f},{-0.527199149f,-0.849741757f},{-0.529803634f,-0.848120332f},{-0.532403111f,-0.84649092f},
{-0.534997642f,-0.84485358f},{-0.537587047f,-0.843208253f},{-0.540171444f,-0.841554999f},{-0.542750776f,-0.839893818f},
{-0.545324981f,-0.838224709f},{-0.547894061f,-0.836547732f},{-0.550457954f,-0.834862888f},{-0.553016722f,-0.833170176f},
{-0.555570245f,-0.831469595f},{-0.558118522f,-0.829761207f},{-0.560661554f,-0.82804507f},{-0.563199341f,-0.826321065f},
{-0.565731823f,-0.824589312f},{-0.568258941f,-0.82284981f},{-0.570780754f,-0.8211025f},{-0.573297143f,-0.819347501f},
{-0.575808167f,-0.817584813f},{-0.578313768f,-0.815814435f},{-0.580813944f,-0.81403631f},{-0.583308637f,-0.812250614f},
{-0.585797846f,-0.81045717f},{-0.588281572f,-0.808656156f},{-0.590759695f,-0.806847572f},{-0.593232274f,-0.805031359f},
{-0.59569931f,-0.803207517f},{-0.598160684f,-0.801376164f},{-0.600616455f,-0.799537241f},{-0.603066623f,-0.797690868f},
{-0.605511069f,-0.795836926f},{-0.607949793f,-0.793975472f},{-0.610382795f,-0.792106569f},{-0.612810075f,-0.790230215f},
{-0.615231574f,-0.78834641f},{-0.61764729f,-0.786455214f},{-0.620057225f,-0.784556568f},{-0.622461259f,-0.78265059f},
{-0.624859512f,-0.780737221f},{-0.627251804f,-0.778816521f},{-0.629638255f,-0.77688849f},{-0.632018745f,-0.774953127f},
{-0.634393275f,-0.773010433f},{-0.636761844f,-0.771060526f},{-0.639124453f,-0.769103348f},{-0.641481042f,-0.767138898f},
{-0.643831551f,-0.765167236f},{-0.64617604f,-0.763188422f},{-0.64851439f,-0.761202395f},{-0.65084666f,-0.759209216f},
{-0.653172851f,-0.757208824f},{-0.655492842f,-0.755201399f},{-0.657806695f,-0.753186822f},{-0.660114348f,-0.751165152f},
{-0.662415802f,-0.749136388f},{-0.664710999f,-0.747100592f},{-0.666999936f,-0.745057762f},{-0.669282615f,-0.743007958f},
{-0.671558976f,-0.740951121f},{-0.673829019f,-0.73888731f},{-0.676092684f,-0.736816585f},{-0.678350031f,-0.734738886f},
{-0.680601001f,-0.732654274f},{-0.682845533f,-0.730562747f},{-0.685083687f,-0.728464365f},{-0.687315345f,-0.726359129f},
{-0.689540565f,-0.724247098f},{-0.691759229f,-0.722128212f},{-0.693971455f,-0.720002532f},{-0.696177125f,-0.717870057f},
{-0.698376238f,-0.715730846f},{-0.700568795f,-0.71358484f},{-0.702754736f,-0.711432219f},{-0.704934061f,-0.709272802f},
{-0.707106769f,-0.707106769f},{-0.709272802f,-0.704934061f},{-0.711432219f,-0.702754736f},{-0.71358484f,-0.700568795f},
{-0.715730846f,-0.698376238f},{-0.717870057f,-0.696177125f},{-0.720002532f,-0.693971455f},{-0.722128212f,-0.691759229f},
{-0.724247098f,-0.689540565f},{-0.726359129f,-0.687315345f},{-0.728464365f,-0.685083687f},{-0.730562747f,-0.682845533f},
{-0.732654274f,-0.680601001f},{-0.734738886f,-0.678350031f},{-0.736816585f,-0.676092684f},{-0.73888731f,-0.673829019f},
{-0.740951121f,-0.671558976f},{-0.743007958f,-0.669282615f},{-0.745057762f,-0.666999936f},{-0.747100592f,-0.664710999f},
{-0.749136388f,-0.662415802f},{-0.751165152f,-0.660114348f},{-0.753186822f,-0.657806695f},{-0.755201399f,-0.655492842f},
{-0.757208824f,-0.653172851f},{-0.759209216f,-0.65084666f},{-0.761202395f,-0.64851439f},{-0.763188422f,-0.64617604f},
{-0.765167236f,-0.643831551f},{-0.767138898f,-0.641481042f},{-0.769103348f,-0.639124453f},{-0.771060526f,-0.636761844f},
{-0.773010433f,-0.634393275f},{-0.774953127f,-0.632018745f},{-0.77688849f,-0.629638255f},{-0.778816521f,-0.627251804f},
{-0.780737221f,-0.624859512f},{-0.78265059f,-0.622461259f},{-0.784556568f,-0.620057225f},{-0.786455214f,-0.61764729f},
{-0.78834641f,-0.615231574f},{-0.790230215f,-0.612810075f},{-0.792106569f,-0.610382795f},{-0.793975472f,-0.607949793f},
{-0.795836926f,-0.605511069f},{-0.797690868f,-0.603066623f},{-0.799537241f,-0.600616455f},{-0.801376164f,-0.598160684f},
{-0.803207517f,-0.59569931f},{-0.805031359f,-0.593232274f},{-0.806847572f,-0.590759695f},{-0.808656156f,-0.588281572f},
{-0.81045717f,-0.585797846f},{-0.812250614f,-0.583308637f},{-0.81403631f,-0.580813944f},{-0.815814435f,-0.578313768f},
{-0.817584813f,-0.575808167f},{-0.819347501f,-0.573297143f},{-0.8211025f,-0.570780754f},{-0.82284981f,-0.568258941f},
{-0.824589312f,-0.565731823f},{-0.826321065f,-0.563199341f},{-0.82804507f,-0.560661554f},{-0.829761207f,-0.558118522f},
{-0.831469595f,-0.555570245f},{-0.833170176f,-0.553016722f},{-0.834862888f,-0.550457954f},{-0.836547732f,-0.547894061f},
{-0.838224709f,-0.545324981f},{-0.839893818f,-0.542750776f},{-0.841554999f,-0.540171444f},{-0.843208253f,-0.537587047f},
{-0.84485358f,-0.534997642f},{-0.84649092f,-0.532403111f},{-0.848120332f,-0.529803634f},{-0.849741757f,-0.527199149f},
{-0.851355195f,-0.524589658f},{-0.852960587f,-0.521975279f},{-0.854557991f,-0.519356012f},{-0.856147349f,-0.516731799f},
{-0.857728601f,-0.514102757f},{-0.859301805f,-0.511468828f},{-0.860866964f,-0.50883013f},{-0.862423956f,-0.506186664f},
{-0.863972843f,-0.50353837f},{-0.865513623f,-0.500885367f},{-0.867046237f,-0.498227656f},{-0.868570685f,-0.495565265f},
{-0.870086968f,-0.492898196f},{-0.871595085f,-0.490226477f},{-0.873094976f,-0.487550169f},{-0.874586642f,-0.484869242f},
{-0.876070082f,-0.482183784f},{-0.877545297f,-0.479493767f},{-0.879012227f,-0.47679922f},{-0.880470872f,-0.474100202f},
{-0.881921291f,-0.471396744f},{-0.883363366f,-0.468688816f},{-0.884797096f,-0.465976506f},{-0.886222541f,-0.463259786f},
{-0.887639642f,-0.460538715f},{-0.889048338f,-0.457813293f},{-0.890448749f,-0.455083579f},{-0.891840696f,-0.452349573f},
{-0.893224299f,-0.449611336f},{-0.894599497f,-0.446868837f},{-0.895966232f,-0.444122136f},{-0.897324562f,-0.441371262f},
{-0.898674488f,-0.438616246f},{-0.900015891f,-0.435857087f},{-0.901348829f,-0.433093816f},{-0.902673304f,-0.430326492f},
{-0.903989315f,-0.427555084f},{-0.905296743f,-0.424779683f},{-0.906595707f,-0.422000259f},{-0.907886088f,-0.419216901f},
{-0.909168005f,-0.416429549f},{-0.910441279f,-0.413638324f},{-0.91170603f,-0.410843164f},{-0.912962198f,-0.408044159f},
{-0.914209783f,-0.405241311f},{-0.915448725f,-0.402434647f},{-0.916679084f,-0.399624199f},{-0.917900801f,-0.396809995f},
{-0.919113874f,-0.393992037f},{-0.920318305f,-0.391170382f},{-0.921514034f,-0.388345033f},{-0.92270112f,-0.385516047f},
{-0.923879504f,-0.382683426f},{-0.925049245f,-0.379847199f},{-0.926210225f,-0.377007425f},{-0.927362502f,-0.374164075f},
{-0.928506076f,-0.371317208f},{-0.929640889f,-0.368466824f},{-0.93076694f,-0.365612984f},{-0.931884289f,-0.362755716f},
{-0.932992816f,-0.359895051f},{-0.934092522f,-0.357030958f},{-0.935183525f,-0.354163527f},{-0.936265647f,-0.351292759f},
{-0.937339008f,-0.348418683f},{-0.938403547f,-0.345541328f},{-0.939459205f,-0.342660725f},{-0.940506041f,-0.339776874f},
{-0.941544056f,-0.336889863f},{-0.94257319f,-0.333999664f},{-0.943593442f,-0.331106305f},{-0.944604814f,-0.328209847f},
{-0.945607305f,-0.32531029f},{-0.946600914f,-0.322407693f},{-0.947585583f,-0.319502026f},{-0.94856137f,-0.316593379f},
{-0.949528158f,-0.313681751f},{-0.950486064f,-0.310767144f},{-0.95143503f,-0.307849646f},{-0.952374995f,-0.304929227f},
{-0.953306019f,-0.302005947f},{-0.954228103f,-0.299079835f},{-0.955141187f,-0.296150893f},{-0.95604527f,-0.293219149f},
{-0.956940353f,-0.290284663f},{-0.957826436f,-0.287347466f},{-0.958703458f,-0.284407526f},{-0.95957154f,-0.281464934f},
{-0.960430503f,-0.27851969f},{-0.961280465f,-0.275571823f},{-0.962121427f,-0.272621363f},{-0.962953269f,-0.269668311f},
{-0.963776052f,-0.266712755f},{-0.964589775f,-0.263754666f},{-0.965394437f,-0.260794103f},{-0.966189981f,-0.257831097f},
{-0.966976464f,-0.254865646f},{-0.967753828f,-0.251897812f},{-0.968522072f,-0.248927608f},{-0.969281256f,-0.24595505f},
{-0.970031261f,-0.242980182f},{-0.970772147f,-0.24000302f},{-0.971503913f,-0.237023607f},{-0.972226501f,-0.234041959f},
{-0.972939968f,-0.231058106f},{-0.973644257f,-0.228072077f},{-0.974339366f,-0.225083917f},{-0.975025356f,-0.222093627f},
{-0.975702107f,-0.219101235f},{-0.976369739f,-0.216106802f},{-0.977028131f,-0.213110313f},{-0.977677345f,-0.210111842f},
{-0.97831738f,-0.207111374f},{-0.978948176f,-0.204108968f},{-0.979569793f,-0.201104641f},{-0.980182111f,-0.198098406f},
{-0.980785251f,-0.195090324f},{-0.981379211f,-0.192080393f},{-0.981963873f,-0.18906866f},{-0.982539296f,-0.186055154f},
{-0.983105481f,-0.183039889f},{-0.983662426f,-0.180022895f},{-0.984210074f,-0.177004218f},{-0.984748483f,-0.173983872f},
{-0.985277653f,-0.170961887f},{-0.985797524f,-0.167938292f},{-0.986308098f,-0.164913118f},{-0.986809373f,-0.161886394f},
{-0.987301409f,-0.15885815f},{-0.987784147f,-0.155828401f},{-0.988257587f,-0.152797192f},{-0.988721669f,-0.149764538f},
{-0.989176512f,-0.146730468f},{-0.989621997f,-0.143695027f},{-0.990058184f,-0.140658244f},{-0.990485072f,-0.137620121f},
{-0.990902662f,-0.134580702f},{-0.991310835f,-0.13154003f},{-0.991709769f,-0.128498107f},{-0.992099285f,-0.125454977f},
{-0.992479563f,-0.122410677f},{-0.992850423f,-0.119365215f},{-0.993211925f,-0.116318628f},{-0.993564129f,-0.113270953f},
{-0.993906975f,-0.110222206f},{-0.994240463f,-0.107172422f},{-0.994564593f,-0.104121633f},{-0.994879305f,-0.10106986f},
{-0.99518472f,-0.0980171412f},{-0.995480776f,-0.0949634984f},{-0.995767415f,-0.0919089541f},{-0.996044695f,-0.0888535529f},
{-0.996312618f,-0.0857973099f},{-0.996571124f,-0.0827402622f},{-0.996820271f,-0.0796824396f},{-0.997060061f,-0.0766238645f},
{-0.997290432f,-0.0735645667f},{-0.997511446f,-0.070504576f},{-0.997723043f,-0.0674439222f},{-0.997925282f,-0.0643826276f},
{-0.998118103f,-0.061320737f},{-0.998301566f,-0.0582582653f},{-0.998475552f,-0.0551952459f},{-0.998640239f,-0.052131705f},
{-0.99879545f,-0.0490676761f},{-0.998941302f,-0.0460031815f},{-0.999077737f,-0.0429382585f},{-0.999204755f,-0.0398729257f},
{-0.999322355f,-0.0368072242f},{-0.999430597f,-0.0337411724f},{-0.999529421f,-0.030674804f},{-0.999618828f,-0.027608145f},
{-0.999698818f,-0.024541229f},{-0.99976939f,-0.0214740802f},{-0.999830604f,-0.0184067301f},{-0.99988234f,-0.015339206f},
{-0.999924719f,-0.0122715384f},{-0.999957621f,-0.00920375437f},{-0.999981165f,-0.00613588467f},{-0.999995291f,-0.00306795677f},
{-1.0f,-1.22464685e-16f},{-0.999995291f,0.00306795677f},{-0.999981165f,0.00613588467f},{-0.999957621f,0.00920375437f},
{-0.999924719f,0.0122715384f},{-0.99988234f,0.015339206f},{-0.999830604f,0.0184067301f},{-0.99976939f,0.0214740802f},
{-0.999698818f,0.024541229f},{-0.999618828f,0.027608145f},{-0.999529421f,0.030674804f},{-0.999430597f,0.0337411724f},
{-0.999322355f,0.0368072242f},{-0.999204755f,0.0398729257f},{-0.999077737f,0.0429382585f},{-0.998941302f,0.0460031815f},
{-0.99879545f,0.0490676761f},{-0.998640239f,0.052131705f},{-0.998475552f,0.0551952459f},{-0.998301566f,0.0582582653f},
{-0.998118103f,0.061320737f},{-0.997925282f,0.0643826276f},{-0.997723043f,0.0674439222f},{-0.997511446f,0.070504576f},
{-0.997290432f,0.0735645667f},{-0.997060061f,0.0766238645f},{-0.996820271f,0.0796824396f},{-0.996571124f,0.0827402622f},
{-0.996312618f,0.0857973099f},{-0.996044695f,0.0888535529f},{-0.995767415f,0.0919089541f},{-0.995480776f,0.0949634984f},
{-0.99518472f,0.0980171412f},{-0.994879305f,0.10106986f},{-0.994564593f,0.104121633f},{-0.994240463f,0.107172422f},
{-0.993906975f,0.110222206f},{-0.993564129f,0.113270953f},{-0.993211925f,0.116318628f},{-0.992850423f,0.119365215f},
{-0.992479563f,0.122410677f},{-0.992099285f,0.125454977f},{-0.991709769f,0.128498107f},{-0.991310835f,0.13154003f},
{-0.990902662f,0.134580702f},{-0.990485072f,0.137620121f},{-0.990058184f,0.140658244f},{-0.989621997f,0.143695027f},
{-0.989176512f,0.146730468f},{-0.988721669f,0.149764538f},{-0.988257587f,0.152797192f},{-0.987784147f,0.155828401f},
{-0.987301409f,0.15885815f},{-0.986809373f,0.161886394f},{-0.986308098f,0.164913118f},{-0.985797524f,0.167938292f},
{-0.985277653f,0.170961887f},{-0.984748483f,0.173983872f},{-0.984210074f,0.177004218f},{-0.983662426f,0.180022895f},
{-0.983105481f,0.183039889f},{-0.982539296f,0.186055154f},{-0.981963873f,0.18906866f},{-0.981379211f,0.192080393f},
{-0.980785251f,0.195090324f},{-0.980182111f,0.198098406f},{-0.979569793f,0.201104641f},{-0.978948176f,0.204108968f},
{-0.97831738f,0.207111374f},{-0.977677345f,0.210111842f},{-0.977028131f,0.213110313f},{-0.976369739f,0.216106802f},
{-0.975702107f,0.219101235f},{-0.975025356f,0.222093627f},{-0.974339366f,0.225083917f},{-0.973644257f,0.228072077f},
{-0.972939968f,0.231058106f},{-0.972226501f,0.234041959f},{-0.971503913f,0.237023607f},{-0.970772147f,0.24000302f},
{-0.970031261f,0.242980182f},{-0.969281256f,0.24595505f},{-0.968522072f,0.248927608f},{-0.967753828f,0.251897812f},
{-0.966976464f,0.254865646f},{-0.966189981f,0.257831097f},{-0.965394437f,0.260794103f},{-0.964589775f,0.263754666f},
{-0.963776052f,0.266712755f},{-0.962953269f,0.269668311f},{-0.962121427f,0.272621363f},{-0.961280465f,0.275571823f},
{-0.960430503f,0.27851969f},{-0.95957154f,0.281464934f},{-0.958703458f,0.284407526f},{-0.957826436f,0.287347466f},
{-0.956940353f,0.290284663f},{-0.95604527f,0.293219149f},{-0.955141187f,0.296150893f},{-0.954228103f,0.299079835f},
{-0.953306019f,0.302005947f},{-0.952374995f,0.304929227f},{-0.95143503f,0.307849646f},{-0.950486064f,0.310767144f},
{-0.949528158f,0.313681751f},{-0.94856137f,0.316593379f},{-0.947585583f,0.319502026f},{-0.946600914f,0.322407693f},
{-0.945607305f,0.32531029f},{-0.944604814f,0.328209847f},{-0.943593442f,0.331106305f},{-0.94257319f,0.333999664f},
{-0.941544056f,0.336889863f},{-0.940506041f,0.339776874f},{-0.939459205f,0.342660725f},{-0.938403547f,0.345541328f},
{-0.937339008f,0.348418683f},{-0.936265647f,0.351292759f},{-0.935183525f,0.354163527f},{-0.934092522f,0.357030958f},
{-0.932992816f,0.359895051f},{-0.931884289f,0.362755716f},{-0.93076694f,0.365612984f},{-0.929640889f,0.368466824f},
{-0.928506076f,0.371317208f},{-0.927362502f,0.374164075f},{-0.926210225f,0.377007425f},{-0.925049245f,0.379847199f},
{-0.923879504f,0.382683426f},{-0.92270112f,0.385516047f},{-0.921514034f,0.388345033f},{-0.920318305f,0.391170382f},
{-0.919113874f,0.393992037f},{-0.917900801f,0.396809995f},{-0.916679084f,0.399624199f},{-0.915448725f,0.402434647f},
{-0.914209783f,0.405241311f},{-0.912962198f,0.408044159f},{-0.91170603f,0.410843164f},{-0.910441279f,0.413638324f},
{-0.909168005f,0.416429549f},{-0.907886088f,0.419216901f},{-0.906595707f,0.422000259f},{-0.905296743f,0.424779683f},
{-0.903989315f,0.427555084f},{-0.902673304f,0.430326492f},{-0.901348829f,0.433093816f},{-0.900015891f,0.435857087f},
{-0.898674488f,0.438616246f},{-0.897324562f,0.441371262f},{-0.895966232f,0.444122136f},{-0.894599497f,0.446868837f},
{-0.893224299f,0.449611336f},{-0.891840696f,0.452349573f},{-0.890448749f,0.455083579f},{-0.889048338f,0.457813293f},
{-0.887639642f,0.460538715f},{-0.886222541f,0.463259786f},{-0.884797096f,0.465976506f},{-0.883363366f,0.468688816f},
{-0.881921291f,0.471396744f},{-0.880470872f,0.474100202f},{-0.879012227f,0.47679922f},{-0.877545297f,0.479493767f},
{-0.876070082f,0.482183784f},{-0.874586642f,0.484869242f},{-0.873094976f,0.487550169f},{-0.871595085f,0.490226477f},
{-0.870086968f,0.492898196f},{-0.868570685f,0.495565265f},{-0.867046237f,0.498227656f},{-0.865513623f,0.500885367f},
{-0.863972843f,0.50353837f},{-0.862423956f,0.506186664f},{-0.860866964f,0.50883013f},{-0.859301805f,0.511468828f},
{-0.857728601f,0.514102757f},{-0.856147349f,0.516731799f},{-0.854557991f,0.519356012f},{-0.852960587f,0.521975279f},
{-0.851355195f,0.524589658f},{-0.849741757f,0.527199149f},{-0.848120332f,0.529803634f},{-0.84649092f,0.532403111f},
{-0.84485358f,0.534997642f},{-0.843208253f,0.537587047f},{-0.841554999f,0.540171444f},{-0.839893818f,0.542750776f},
{-0.838224709f,0.545324981f},{-0.836547732f,0.547894061f},{-0.834862888f,0.550457954f},{-0.833170176f,0.553016722f},
{-0.831469595f,0.555570245f},{-0.829761207f,0.558118522f},{-0.82804507f,0.560661554f},{-0.826321065f,0.563199341f},
{-0.824589312f,0.565731823f},{-0.82284981f,0.568258941f},{-0.8211025f,0.570780754f},{-0.819347501f,0.573297143f},
{-0.817584813f,0.575808167f},{-0.815814435f,0.578313768f},{-0.81403631f,0.580813944f},{-0.812250614f,0.583308637f},
{-0.81045717f,0.585797846f},{-0.808656156f,0.588281572f},{-0.806847572f,0.590759695f},{-0.805031359f,0.593232274f},
{-0.803207517f,0.59569931f},{-0.801376164f,0.598160684f},{-0.799537241f,0.600616455f},{-0.797690868f,0.603066623f},
{-0.795836926f,0.605511069f},{-0.793975472f,0.607949793f},{-0.792106569f,0.610382795f},{-0.790230215f,0.612810075f},
{-0.78834641f,0.615231574f},{-0.786455214f,0.61764729f},{-0.784556568f,0.620057225f},{-0.78265059f,0.622461259f},
{-0.780737221f,0.624859512f},{-0.778816521f,0.627251804f},{-0.77688849f,0.629638255f},{-0.774953127f,0.632018745f},
{-0.773010433f,0.634393275f},{-0.771060526f,0.636761844f},{-0.769103348f,0.639124453f},{-0.767138898f,0.641481042f},
{-0.765167236f,0.643831551f},{-0.763188422f,0.64617604f},{-0.761202395f,0.64851439f},{-0.759209216f,0.65084666f},
{-0.757208824f,0.653172851f},{-0.755201399f,0.655492842f},{-0.753186822f,0.657806695f},{-0.751165152f,0.660114348f},
{-0.749136388f,0.662415802f},{-0.747100592f,0.664710999f},{-0.745057762f,0.666999936f},{-0.743007958f,0.669282615f},
{-0.740951121f,0.671558976f},{-0.73888731f,0.673829019f},{-0.736816585f,0.676092684f},{-0.734738886f,0.678350031f},
{-0.732654274f,0.680601001f},{-0.730562747f,0.682845533f},{-0.728464365f,0.685083687f},{-0.726359129f,0.687315345f},
{-0.724247098f,0.689540565f},{-0.722128212f,0.691759229f},{-0.720002532f,0.693971455f},{-0.717870057f,0.696177125f},
{-0.715730846f,0.698376238f},{-0.71358484f,0.700568795f},{-0.711432219f,0.702754736f},{-0.709272802f,0.704934061f},
{-0.707106769f,0.707106769f},{-0.704934061f,0.709272802f},{-0.702754736f,0.711432219f},{-0.700568795f,0.71358484f},
{-0.698376238f,0.715730846f},{-0.696177125f,0.717870057f},{-0.693971455f,0.720002532f},{-0.691759229f,0.722128212f},
{-0.689540565f,0.724247098f},{-0.687315345f,0.726359129f},{-0.685083687f,0.728464365f},{-0.682845533f,0.730562747f},
{-0.680601001f,0.732654274f},{-0.678350031f,0.734738886f},{-0.676092684f,0.736816585f},{-0.673829019f,0.73888731f},
{-0.671558976f,0.740951121f},{-0.669282615f,0.743007958f},{-0.666999936f,0.745057762f},{-0.664710999f,0.747100592f},
{-0.662415802f,0.749136388f},{-0.660114348f,0.751165152f},{-0.657806695f,0.753186822f},{-0.655492842f,0.755201399f},
{-0.653172851f,0.757208824f},{-0.65084666f,0.759209216f},{-0.64851439f,0.761202395f},{-0.64617604f,0.763188422f},
{-0.643831551f,0.765167236f},{-0.641481042f,0.767138898f},{-0.639124453f,0.769103348f},{-0.636761844f,0.771060526f},
{-0.634393275f,0.773010433f},{-0.632018745f,0.774953127f},{-0.629638255f,0.77688849f},{-0.627251804f,0.778816521f},
{-0.624859512f,0.780737221f},{-0.622461259f,0.78265059f},{-0.620057225f,0.784556568f},{-0.61764729f,0.786455214f},
{-0.615231574f,0.78834641f},{-0.612810075f,0.790230215f},{-0.610382795f,0.792106569f},{-0.607949793f,0.793975472f},
{-0.605511069f,0.795836926f},{-0.603066623f,0.797690868f},{-0.600616455f,0.799537241f},{-0.598160684f,0.801376164f},
{-0.59569931f,0.803207517f},{-0.593232274f,0.805031359f},{-0.590759695f,0.806847572f},{-0.588281572f,0.808656156f},
{-0.585797846f,0.81045717f},{-0.583308637f,0.812250614f},{-0.580813944f,0.81403631f},{-0.578313768f,0.815814435f},
{-0.575808167f,0.817584813f},{-0.573297143f,0.819347501f},{-0.570780754f,0.8211025f},{-0.568258941f,0.82284981f},
{-0.565731823f,0.824589312f},{-0.563199341f,0.826321065f},{-0.560661554f,0.82804507f},{-0.558118522f,0.829761207f},
{-0.555570245f,0.831469595f},{-0.553016722f,0.833170176f},{-0.550457954f,0.834862888f},{-0.547894061f,0.836547732f},
{-0.545324981f,0.838224709f},{-0.542750776f,0.839893818f},{-0.540171444f,0.841554999f},{-0.537587047f,0.843208253f},
{-0.534997642f,0.84485358f},{-0.532403111f,0.84649092f},{-0.529803634f,0.848120332f},{-0.527199149f,0.849741757f},
{-0.524589658f,0.851355195f},{-0.521975279f,0.852960587f},{-0.519356012f,0.854557991f},{-0.516731799f,0.856147349f},
{-0.514102757f,0.857728601f},{-0.511468828f,0.859301805f},{-0.50883013f,0.860866964f},{-0.506186664f,0.862423956f},
{-0.50353837f,0.863972843f},{-0.500885367f,0.865513623f},{-0.498227656f,0.867046237f},{-0.495565265f,0.868570685f},
{-0.492898196f,0.870086968f},{-0.490226477f,0.871595085f},{-0.487550169f,0.873094976f},{-0.484869242f,0.874586642f},
{-0.482183784f,0.876070082f},{-0.479493767f,0.877545297f},{-0.47679922f,0.879012227f},{-0.474100202f,0.880470872f},
{-0.471396744f,0.881921291f},{-0.468688816f,0.883363366f},{-0.465976506f,0.884797096f},{-0.463259786f,0.886222541f},
{-0.460538715f,0.887639642f},{-0.457813293f,0.889048338f},{-0.455083579f,0.890448749f},{-0.452349573f,0.891840696f},
{-0.449611336f,0.893224299f},{-0.446868837f,0.894599497f},{-0.444122136f,0.895966232f},{-0.441371262f,0.897324562f},
{-0.438616246f,0.898674488f},{-0.435857087f,0.900015891f},{-0.433093816f,0.901348829f},{-0.430326492f,0.902673304f},
{-0.427555084f,0.903989315f},{-0.424779683f,0.905296743f},{-0.422000259f,0.906595707f},{-0.419216901f,0.907886088f},
{-0.416429549f,0.909168005f},{-0.413638324f,0.910441279f},{-0.410843164f,0.91170603f},{-0.408044159f,0.912962198f},
{-0.405241311f,0.914209783f},{-0.402434647f,0.915448725f},{-0.399624199f,0.916679084f},{-0.396809995f,0.917900801f},
{-0.393992037f,0.919113874f},{-0.391170382f,0.920318305f},{-0.388345033f,0.921514034f},{-0.385516047f,0.92270112f},
{-0.382683426f,0.923879504f},{-0.379847199f,0.925049245f},{-0.377007425f,0.926210225f},{-0.374164075f,0.927362502f},
{-0.371317208f,0.928506076f},{-0.368466824f,0.929640889f},{-0.365612984f,0.93076694f},{-0.362755716f,0.931884289f},
{-0.359895051f,0.932992816f},{-0.357030958f,0.934092522f},{-0.354163527f,0.935183525f},{-0.351292759f,0.936265647f},
{-0.348418683f,0.937339008f},{-0.345541328f,0.938403547f},{-0.342660725f,0.939459205f},{-0.339776874f,0.940506041f},
{-0.336889863f,0.941544056f},{-0.333999664f,0.94257319f},{-0.331106305f,0.943593442f},{-0.328209847f,0.944604814f},
{-0.32531029f,0.945607305f},{-0.322407693f,0.946600914f},{-0.319502026f,0.947585583f},{-0.316593379f,0.94856137f},
{-0.313681751f,0.949528158f},{-0.310767144f,0.950486064f},{-0.307849646f,0.95143503f},{-0.304929227f,0.952374995f},
{-0.302005947f,0.953306019f},{-0.299079835f,0.954228103f},{-0.296150893f,0.955141187f},{-0.293219149f,0.95604527f},
{-0.290284663f,0.956940353f},{-0.287347466f,0.957826436f},{-0.284407526f,0.958703458f},{-0.281464934f,0.95957154f},
{-0.27851969f,0.960430503f},{-0.275571823f,0.961280465f},{-0.272621363f,0.962121427f},{-0.269668311f,0.962953269f},
{-0.266712755f,0.963776052f},{-0.263754666f,0.964589775f},{-0.260794103f,0.965394437f},{-0.257831097f,0.966189981f},
{-0.254865646f,0.966976464f},{-0.251897812f,0.967753828f},{-0.248927608f,0.968522072f},{-0.24595505f,0.969281256f},
{-0.242980182f,0.970031261f},{-0.24000302f,0.970772147f},{-0.237023607f,0.971503913f},{-0.234041959f,0.972226501f},
{-0.231058106f,0.972939968f},{-0.228072077f,0.973644257f},{-0.225083917f,0.974339366f},{-0.222093627f,0.975025356f},
{-0.219101235f,0.975702107f},{-0.216106802f,0.976369739f},{-0.213110313f,0.977028131f},{-0.210111842f,0.977677345f},
{-0.207111374f,0.97831738f},{-0.204108968f,0.978948176f},{-0.201104641f,0.979569793f},{-0.198098406f,0.980182111f},
{-0.195090324f,0.980785251f},{-0.192080393f,0.981379211f},{-0.18906866f,0.981963873f},{-0.186055154f,0.982539296f},
{-0.183039889f,0.983105481f},{-0.180022895f,0.983662426f},{-0.177004218f,0.984210074f},{-0.173983872f,0.984748483f},
{-0.170961887f,0.985277653f},{-0.167938292f,0.985797524f},{-0.164913118f,0.986308098f},{-0.161886394f,0.986809373f},
{-0.15885815f,0.987301409f},{-0.155828401f,0.987784147f},{-0.152797192f,0.988257587f},{-0.149764538f,0.988721669f},
{-0.146730468f,0.989176512f},{-0.143695027f,0.989621997f},{-0.140658244f,0.990058184f},{-0.137620121f,0.990485072f},
{-0.134580702f,0.990902662f},{-0.13154003f,0.991310835f},{-0.128498107f,0.991709769f},{-0.125454977f,0.992099285f},
{-0.122410677f,0.992479563f},{-0.119365215f,0.992850423f},{-0.116318628f,0.993211925f},{-0.113270953f,0.993564129f},
{-0.110222206f,0.993906975f},{-0.107172422f,0.994240463f},{-0.104121633f,0.994564593f},{-0.10106986f,0.994879305f},
{-0.0980171412f,0.99518472f},{-0.0949634984f,0.995480776f},{-0.0919089541f,0.995767415f},{-0.0888535529f,0.996044695f},
{-0.0857973099f,0.996312618f},{-0.0827402622f,0.996571124f},{-0.0796824396f,0.996820271f},{-0.0766238645f,0.997060061f},
{-0.0735645667f,0.997290432f},{-0.070504576f,0.997511446f},{-0.0674439222f,0.997723043f},{-0.0643826276f,0.997925282f},
{-0.061320737f,0.998118103f},{-0.0582582653f,0.998301566f},{-0.0551952459f,0.998475552f},{-0.052131705f,0.998640239f},
{-0.0490676761f,0.99879545f},{-0.0460031815f,0.998941302f},{-0.0429382585f,0.999077737f},{-0.0398729257f,0.999204755f},
{-0.0368072242f,0.999322355f},{-0.0337411724f,0.999430597f},{-0.030674804f,0.999529421f},{-0.027608145f,0.999618828f},
{-0.024541229f,0.999698818f},{-0.0214740802f,0.99976939f},{-0.0184067301f,0.999830604f},{-0.015339206f,0.99988234f},
{-0.0122715384f,0.999924719f},{-0.00920375437f,0.999957621f},{-0.00613588467f,0.999981165f},{-0.00306795677f,0.999995291f},
{-1.83697015e-16f,1.0f},{0.00306795677f,0.999995291f},{0.00613588467f,0.999981165f},{0.00920375437f,0.999957621f},
{0.0122715384f,0.999924719f},{0.015339206f,0.99988234f},{0.0184067301f,0.999830604f},{0.0214740802f,0.99976939f},
{0.024541229f,0.999698818f},{0.027608145f,0.999618828f},{0.030674804f,0.999529421f},{0.0337411724f,0.999430597f},
{0.0368072242f,0.999322355f},{0.0398729257f,0.999204755f},{0.0429382585f,0.999077737f},{0.0460031815f,0.998941302f},
{0.0490676761f,0.99879545f},{0.052131705f,0.998640239f},{0.0551952459f,0.998475552f},{0.0582582653f,0.998301566f},
{0.061320737f,0.998118103f},{0.0643826276f,0.997925282f},{0.0674439222f,0.997723043f},{0.070504576f,0.997511446f},
{0.0735645667f,0.997290432f},{0.0766238645f,0.997060061f},{0.0796824396f,0.996820271f},{0.0827402622f,0.996571124f},
{0.0857973099f,0.996312618f},{0.0888535529f,0.996044695f},{0.0919089541f,0.995767415f},{0.0949634984f,0.995480776f},
{0.0980171412f,0.99518472f},{0.10106986f,0.994879305f},{0.104121633f,0.994564593f},{0.107172422f,0.994240463f},
{0.110222206f,0.993906975f},{0.113270953f,0.993564129f},{0.116318628f,0.993211925f},{0.119365215f,0.992850423f},
{0.122410677f,0.992479563f},{0.125454977f,0.992099285f},{0.128498107f,0.991709769f},{0.13154003f,0.991310835f},
{0.134580702f,0.990902662f},{0.137620121f,0.990485072f},{0.140658244f,0.990058184f},{0.143695027f,0.989621997f},
{0.146730468f,0.989176512f},{0.149764538f,0.988721669f},{0.152797192f,0.988257587f},{0.155828401f,0.987784147f},
{0.15885815f,0.987301409f},{0.161886394f,0.986809373f},{0.164913118f,0.986308098f},{0.167938292f,0.985797524f},
{0.170961887f,0.985277653f},{0.173983872f,0.984748483f},{0.177004218f,0.984210074f},{0.180022895f,0.983662426f},
{0.183039889f,0.983105481f},{0.186055154f,0.982539296f},{0.18906866f,0.981963873f},{0.192080393f,0.981379211f},
{0.195090324f,0.980785251f},{0.198098406f,0.980182111f},{0.201104641f,0.979569793f},{0.204108968f,0.978948176f},
{0.207111374f,0.97831738f},{0.210111842f,0.977677345f},{0.213110313f,0.977028131f},{0.216106802f,0.976369739f},
{0.219101235f,0.975702107f},{0.222093627f,0.975025356f},{0.225083917f,0.974339366f},{0.228072077f,0.973644257f},
{0.231058106f,0.972939968f},{0.234041959f,0.972226501f},{0.237023607f,0.971503913f},{0.24000302f,0.970772147f},
{0.242980182f,0.970031261f},{0.24595505f,0.969281256f},{0.248927608f,0.968522072f},{0.251897812f,0.967753828f},
{0.254865646f,0.966976464f},{0.257831097f,0.966189981f},{0.260794103f,0.965394437f},{0.263754666f,0.964589775f},
{0.266712755f,0.963776052f},{0.269668311f,0.962953269f},{0.272621363f,0.962121427f},{0.275571823f,0.961280465f},
{0.27851969f,0.960430503f},{0.281464934f,0.95957154f},{0.284407526f,0.958703458f},{0.287347466f,0.957826436f},
{0.290284663f,0.956940353f},{0.293219149f,0.95604527f},{0.296150893f,0.955141187f},{0.299079835f,0.954228103f},
{0.302005947f,0.953306019f},{0.304929227f,0.952374995f},{0.307849646f,0.95143503f},{0.310767144f,0.950486064f},
{0.313681751f,0.949528158f},{0.316593379f,0.94856137f},{0.319502026f,0.947585583f},{0.322407693f,0.946600914f},
{0.32531029f,0.945607305f},{0.328209847f,0.944604814f},{0.331106305f,0.943593442f},{0.333999664f,0.94257319f},
{0.336889863f,0.941544056f},{0.339776874f,0.940506041f},{0.342660725f,0.939459205f},{0.345541328f,0.938403547f},
{0.348418683f,0.937339008f},{0.351292759f,0.936265647f},{0.354163527f,0.935183525f},{0.357030958f,0.934092522f},
{0.359895051f,0.932992816f},{0.362755716f,0.931884289f},{0.365612984f,0.93076694f},{0.368466824f,0.929640889f},
{0.371317208f,0.928506076f},{0.374164075f,0.927362502f},{0.377007425f,0.926210225f},{0.379847199f,0.925049245f},
{0.382683426f,0.923879504f},{0.385516047f,0.92270112f},{0.388345033f,0.921514034f},{0.391170382f,0.920318305f},
{0.393992037f,0.919113874f},{0.396809995f,0.917900801f},{0.399624199f,0.916679084f},{0.402434647f,0.915448725f},
{0.405241311f,0.914209783f},{0.408044159f,0.912962198f},{0.410843164f,0.91170603f},{0.413638324f,0.910441279f},
{0.416429549f,0.909168005f},{0.419216901f,0.907886088f},{0.422000259f,0.906595707f},{0.424779683f,0.905296743f},
{0.427555084f,0.903989315f},{0.430326492f,0.902673304f},{0.433093816f,0.901348829f},{0.435857087f,0.900015891f},
{0.438616246f,0.898674488f},{0.441371262f,0.897324562f},{0.444122136f,0.895966232f},{0.446868837f,0.894599497f},
{0.449611336f,0.893224299f},{0.452349573f,0.891840696f},{0.455083579f,0.890448749f},{0.457813293f,0.889048338f},
{0.460538715f,0.887639642f},{0.463259786f,0.886222541f},{0.465976506f,0.884797096f},{0.468688816f,0.883363366f},
{0.471396744f,0.881921291f},{0.474100202f,0.880470872f},{0.47679922f,0.879012227f},{0.479493767f,0.877545297f},
{0.482183784f,0.876070082f},{0.484869242f,0.874586642f},{0.487550169f,0.873094976f},{0.490226477f,0.871595085f},
{0.492898196f,0.870086968f},{0.495565265f,0.868570685f},{0.498227656f,0.867046237f},{0.500885367f,0.865513623f},
{0.50353837f,0.863972843f},{0.506186664f,0.862423956f},{0.50883013f,0.860866964f},{0.511468828f,0.859301805f},
{0.514102757f,0.857728601f},{0.516731799f,0.856147349f},{0.519356012f,0.854557991f},{0.521975279f,0.852960587f},
{0.524589658f,0.851355195f},{0.527199149f,0.849741757f},{0.529803634f,0.848120332f},{0.532403111f,0.84649092f},
{0.534997642f,0.84485358f},{0.537587047f,0.843208253f},{0.540171444f,0.841554999f},{0.542750776f,0.839893818f},
{0.545324981f,0.838224709f},{0.547894061f,0.836547732f},{0.550457954f,0.834862888f},{0.553016722f,0.833170176f},
{0.555570245f,0.831469595f},{0.558118522f,0.829761207f},{0.560661554f,0.82804507f},{0.563199341f,0.826321065f},
{0.565731823f,0.824589312f},{0.568258941f,0.82284981f},{0.570780754f,0.8211025f},{0.573297143f,0.819347501f},
{0.575808167f,0.817584813f},{0.578313768f,0.815814435f},{0.580813944f,0.81403631f},{0.583308637f,0.812250614f},
{0.585797846f,0.81045717f},{0.588281572f,0.808656156f},{0.590759695f,0.806847572f},{0.593232274f,0.805031359f},
{0.59569931f,0.803207517f},{0.598160684f,0.801376164f},{0.600616455f,0.799537241f},{0.603066623f,0.797690868f},
{0.605511069f,0.795836926f},{0.607949793f,0.793975472f},{0.610382795f,0.792106569f},{0.612810075f,0.790230215f},
{0.615231574f,0.78834641f},{0.61764729f,0.786455214f},{0.620057225f,0.784556568f},{0.622461259f,0.78265059f},
{0.624859512f,0.780737221f},{0.627251804f,0.778816521f},{0.629638255f,0.77688849f},{0.632018745f,0.774953127f},
{0.634393275f,0.773010433f},{0.636761844f,0.771060526f},{0.639124453f,0.769103348f},{0.641481042f,0.767138898f},
{0.643831551f,0.765167236f},{0.64617604f,0.763188422f},{0.64851439f,0.761202395f},{0.65084666f,0.759209216f},
{0.653172851f,0.757208824f},{0.655492842f,0.755201399f},{0.657806695f,0.753186822f},{0.660114348f,0.751165152f},
{0.662415802f,0.749136388f},{0.664710999f,0.747100592f},{0.666999936f,0.745057762f},{0.669282615f,0.743007958f},
{0.671558976f,0.740951121f},{0.673829019f,0.73888731f},{0.676092684f,0.736816585f},{0.678350031f,0.734738886f},
{0.680601001f,0.732654274f},{0.682845533f,0.730562747f},{0.685083687f,0.728464365f},{0.687315345f,0.726359129f},
{0.689540565f,0.724247098f},{0.691759229f,0.722128212f},{0.693971455f,0.720002532f},{0.696177125f,0.717870057f},
{0.698376238f,0.715730846f},{0.700568795f,0.71358484f},{0.702754736f,0.711432219f},{0.704934061f,0.709272802f},
{0.707106769f,0.707106769f},{0.709272802f,0.704934061f},{0.711432219f,0.702754736f},{0.71358484f,0.700568795f},
{0.715730846f,0.698376238f},{0.717870057f,0.696177125f},{0.720002532f,0.693971455f},{0.722128212f,0.691759229f},
{0.724247098f,0.689540565f},{0.726359129f,0.687315345f},{0.728464365f,0.685083687f},{0.730562747f,0.682845533f},
{0.732654274f,0.680601001f},{0.734738886f,0.678350031f},{0.736816585f,0.676092684f},{0.73888731f,0.673829019f},
{0.740951121f,0.671558976f},{0.743007958f,0.669282615f},{0.745057762f,0.666999936f},{0.747100592f,0.664710999f},
{0.749136388f,0.662415802f},{0.751165152f,0.660114348f},{0.753186822f,0.657806695f},{0.755201399f,0.655492842f},
{0.757208824f,0.653172851f},{0.759209216f,0.65084666f},{0.761202395f,0.64851439f},{0.763188422f,0.64617604f},
{0.765167236f,0.643831551f},{0.767138898f,0.641481042f},{0.769103348f,0.639124453f},{0.771060526f,0.636761844f},
{0.773010433f,0.634393275f},{0.774953127f,0.632018745f},{0.77688849f,0.629638255f},{0.778816521f,0.627251804f},
{0.780737221f,0.624859512f},{0.78265059f,0.622461259f},{0.784556568f,0.620057225f},{0.786455214f,0.61764729f},
{0.78834641f,0.615231574f},{0.790230215f,0.612810075f},{0.792106569f,0.610382795f},{0.793975472f,0.607949793f},
{0.795836926f,0.605511069f},{0.797690868f,0.603066623f},{0.799537241f,0.600616455f},{0.801376164f,0.598160684f},
{0.803207517f,0.59569931f},{0.805031359f,0.593232274f},{0.806847572f,0.590759695f},{0.808656156f,0.588281572f},
{0.81045717f,0.585797846f},{0.812250614f,0.583308637f},{0.81403631f,0.580813944f},{0.815814435f,0.578313768f},
{0.817584813f,0.575808167f},{0.819347501f,0.573297143f},{0.8211025f,0.570780754f},{0.82284981f,0.568258941f},
{0.824589312f,0.565731823f},{0.826321065f,0.563199341f},{0.82804507f,0.560661554f},{0.829761207f,0.558118522f},
{0.831469595f,0.555570245f},{0.833170176f,0.553016722f},{0.834862888f,0.550457954f},{0.836547732f,0.547894061f},
{0.838224709f,0.545324981f},{0.839893818f,0.542750776f},{0.841554999f,0.540171444f},{0.843208253f,0.537587047f},
{0.84485358f,0.534997642f},{0.84649092f,0.532403111f},{0.848120332f,0.529803634f},{0.849741757f,0.527199149f},
{0.851355195f,0.524589658f},{0.852960587f,0.521975279f},{0.854557991f,0.519356012f},{0.856147349f,0.516731799f},
{0.857728601f,0.514102757f},{0.859301805f,0.511468828f},{0.860866964f,0.50883013f},{0.862423956f,0.506186664f},
{0.863972843f,0.50353837f},{0.865513623f,0.500885367f},{0.867046237f,0.498227656f},{0.868570685f,0.495565265f},
{0.870086968f,0.492898196f},{0.871595085f,0.490226477f},{0.873094976f,0.487550169f},{0.874586642f,0.484869242f},
{0.876070082f,0.482183784f},{0.877545297f,0.479493767f},{0.879012227f,0.47679922f},{0.880470872f,0.474100202f},
{0.881921291f,0.471396744f},{0.883363366f,0.468688816f},{0.884797096f,0.465976506f},{0.886222541f,0.463259786f},
{0.887639642f,0.460538715f},{0.889048338f,0.457813293f},{0.890448749f,0.455083579f},{0.891840696f,0.452349573f},
{0.893224299f,0.449611336f},{0.894599497f,0.446868837f},{0.895966232f,0.444122136f},{0.897324562f,0.441371262f},
{0.898674488f,0.438616246f},{0.900015891f,0.435857087f},{0.901348829f,0.433093816f},{0.902673304f,0.430326492f},
{0.903989315f,0.427555084f},{0.905296743f,0.424779683f},{0.906595707f,0.422000259f},{0.907886088f,0.419216901f},
{0.909168005f,0.416429549f},{0.910441279f,0.413638324f},{0.91170603f,0.410843164f},{0.912962198f,0.408044159f},
{0.914209783f,0.405241311f},{0.915448725f,0.402434647f},{0.916679084f,0.399624199f},{0.917900801f,0.396809995f},
{0.919113874f,0.393992037f},{0.920318305f,0.391170382f},{0.921514034f,0.388345033f},{0.92270112f,0.385516047f},
{0.923879504f,0.382683426f},{0.925049245f,0.379847199f},{0.926210225f,0.377007425f},{0.927362502f,0.374164075f},
{0.928506076f,0.371317208f},{0.929640889f,0.368466824f},{0.93076694f,0.365612984f},{0.931884289f,0.362755716f},
{0.932992816f,0.359895051f},{0.934092522f,0.357030958f},{0.935183525f,0.354163527f},{0.936265647f,0.351292759f},
{0.937339008f,0.348418683f},{0.938403547f,0.345541328f},{0.939459205f,0.342660725f},{0.940506041f,0.339776874f},
{0.941544056f,0.336889863f},{0.94257319f,0.333999664f},{0.943593442f,0.331106305f},{0.944604814f,0.328209847f},
{0.945607305f,0.32531029f},{0.946600914f,0.322407693f},{0.947585583f,0.319502026f},{0.94856137f,0.316593379f},
{0.949528158f,0.313681751f},{0.950486064f,0.310767144f},{0.95143503f,0.307849646f},{0.952374995f,0.304929227f},
{0.953306019f,0.302005947f},{0.954228103f,0.299079835f},{0.955141187f,0.296150893f},{0.95604527f,0.293219149f},
{0.956940353f,0.290284663f},{0.957826436f,0.287347466f},{0.958703458f,0.284407526f},{0.95957154f,0.281464934f},
{0.960430503f,0.27851969f},{0.961280465f,0.275571823f},{0.962121427f,0.272621363f},{0.962953269f,0.269668311f},
{0.963776052f,0.266712755f},{0.964589775f,0.263754666f},{0.965394437f,0.260794103f},{0.966189981f,0.257831097f},
{0.966976464f,0.254865646f},{0.967753828f,0.251897812f},{0.968522072f,0.248927608f},{0.969281256f,0.24595505f},
{0.970031261f,0.242980182f},{0.970772147f,0.24000302f},{0.971503913f,0.237023607f},{0.972226501f,0.234041959f},
{0.972939968f,0.231058106f},{0.973644257f,0.228072077f},{0.974339366f,0.225083917f},{0.975025356f,0.222093627f},
{0.975702107f,0.219101235f},{0.976369739f,0.216106802f},{0.977028131f,0.213110313f},{0.977677345f,0.210111842f},
{0.97831738f,0.207111374f},{0.978948176f,0.204108968f},{0.979569793f,0.201104641f},{0.980182111f,0.198098406f},
{0.980785251f,0.195090324f},{0.981379211f,0.192080393f},{0.981963873f,0.18906866f},{0.982539296f,0.186055154f},
{0.983105481f,0.183039889f},{0.983662426f,0.180022895f},{0.984210074f,0.177004218f},{0.984748483f,0.173983872f},
{0.985277653f,0.170961887f},{0.985797524f,0.167938292f},{0.986308098f,0.164913118f},{0.986809373f,0.161886394f},
{0.987301409f,0.15885815f},{0.987784147f,0.155828401f},{0.988257587f,0.152797192f},{0.988721669f,0.149764538f},
{0.989176512f,0.146730468f},{0.989621997f,0.143695027f},{0.990058184f,0.140658244f},{0.990485072f,0.137620121f},
{0.990902662f,0.134580702f},{0.991310835f,0.13154003f},{0.991709769f,0.128498107f},{0.992099285f,0.125454977f},
{0.992479563f,0.122410677f},{0.992850423f,0.119365215f},{0.993211925f,0.116318628f},{0.993564129f,0.113270953f},
{0.993906975f,0.110222206f},{0.994240463f,0.107172422f},{0.994564593f,0.104121633f},{0.994879305f,0.10106986f},
{0.99518472f,0.0980171412f},{0.995480776f,0.0949634984f},{0.995767415f,0.0919089541f},{0.996044695f,0.0888535529f},
{0.996312618f,0.0857973099f},{0.996571124f,0.0827402622f},{0.996820271f,0.0796824396f},{0.997060061f,0.0766238645f},
{0.997290432f,0.0735645667f},{0.997511446f,0.070504576f},{0.997723043f,0.0674439222f},{0.997925282f,0.0643826276f},
{0.998118103f,0.061320737f},{0.998301566f,0.0582582653f},{0.998475552f,0.0551952459f},{0.998640239f,0.052131705f},
{0.99879545f,0.0490676761f},{0.998941302f,0.0460031815f},{0.999077737f,0.0429382585f},{0.999204755f,0.0398729257f},
{0.999322355f,0.0368072242f},{0.999430597f,0.0337411724f},{0.999529421f,0.030674804f},{0.999618828f,0.027608145f},
{0.999698818f,0.024541229f},{0.99976939f,0.0214740802f},{0.999830604f,0.0184067301f},{0.99988234f,0.015339206f},
{0.999924719f,0.0122715384f},{0.999957621f,0.00920375437f},{0.999981165f,0.00613588467f},{0.999995291f,0.00306795677f},
};
__device__ const float2 c_tw448[448] = {
{1.0f,-0.0f},{0.999901652f,-0.0140245073f},{0.999606609f,-0.0280462559f},{0.99911499f,-0.0420624875f},
{0.998426795f,-0.056070447f},{0.997542262f,-0.0700673759f},{0.996461511f,-0.0840505213f},{0.99518472f,-0.0980171412f},
{0.993712187f,-0.111964479f},{0.99204421f,-0.125889793f},{0.990181148f,-0.139790341f},{0.988123238f,-0.153663397f},
{0.985871017f,-0.167506218f},{0.983424842f,-0.181316108f},{0.980785251f,-0.195090324f},{0.977952778f,-0.208826169f},
{0.974927902f,-0.222520933f},{0.971711278f,-0.236171931f},{0.968303502f,-0.249776483f},{0.964705288f,-0.26333189f},
{0.960917294f,-0.276835501f},{0.956940353f,-0.290284663f},{0.952775121f,-0.303676754f},{0.948422492f,-0.317009091f},
{0.943883359f,-0.330279052f},{0.939158499f,-0.343484074f},{0.934248924f,-0.356621534f},{0.929155588f,-0.369688839f},
{0.923879504f,-0.382683426f},{0.918421745f,-0.395602763f},{0.912783265f,-0.408444256f},{0.906965256f,-0.421205431f},
{0.90096885f,-0.433883727f},{0.894795239f,-0.446476698f},{0.888445616f,-0.458981872f},{0.881921291f,-0.471396744f},
{0.875223398f,-0.483718902f},{0.868353426f,-0.495945901f},{0.861312628f,-0.508075356f},{0.854102433f,-0.520104885f},
{0.846724212f,-0.532032073f},{0.839179456f,-0.543854654f},{0.831469595f,-0.555570245f},{0.823596239f,-0.567176521f},
{0.815560877f,-0.578671277f},{0.80736506f,-0.590052247f},{0.799010456f,-0.601317108f},{0.790498734f,-0.612463653f},
{0.781831503f,-0.623489797f},{0.773010433f,-0.634393275f},{0.764037371f,-0.645172f},{0.754913986f,-0.655823767f},
{0.745642185f,-0.66634655f},{0.736223638f,-0.676738322f},{0.726660311f,-0.686996937f},{0.716954052f,-0.697120428f},
{0.707106769f,-0.707106769f},{0.697120428f,-0.716954052f},{0.686996937f,-0.726660311f},{0.676738322f,-0.736223638f},
{0.66634655f,-0.745642185f},{0.655823767f,-0.754913986f},{0.645172f,-0.764037371f},{0.634393275f,-0.773010433f},
{0.623489797f,-0.781831503f},{0.612463653f,-0.790498734f},{0.601317108f,-0.799010456f},{0.590052247f,-0.80736506f},
{0.578671277f,-0.815560877f},{0.567176521f,-0.823596239f},{0.555570245f,-0.831469595f},{0.543854654f,-0.839179456f},
{0.532032073f,-0.846724212f},{0.520104885f,-0.854102433f},{0.508075356f,-0.861312628f},{0.495945901f,-0.868353426f},
{0.483718902f,-0.875223398f},{0.471396744f,-0.881921291f},{0.458981872f,-0.888445616f},{0.446476698f,-0.894795239f},
{0.433883727f,-0.90096885f},{0.421205431f,-0.906965256f},{0.408444256f,-0.912783265f},{0.395602763f,-0.918421745f},
{0.382683426f,-0.923879504f},{0.369688839f,-0.929155588f},{0.356621534f,-0.934248924f},{0.343484074f,-0.939158499f},
{0.330279052f,-0.943883359f},{0.317009091f,-0.948422492f},{0.303676754f,-0.952775121f},{0.290284663f,-0.956940353f},
{0.276835501f,-0.960917294f},{0.26333189f,-0.964705288f},{0.249776483f,-0.968303502f},{0.236171931f,-0.971711278f},
{0.222520933f,-0.974927902f},{0.208826169f,-0.977952778f},{0.195090324f,-0.980785251f},{0.181316108f,-0.983424842f},
{0.167506218f,-0.985871017f},{0.153663397f,-0.988123238f},{0.139790341f,-0.990181148f},{0.125889793f,-0.99204421f},
{0.111964479f,-0.993712187f},{0.0980171412f,-0.99518472f},{0.0840505213f,-0.996461511f},{0.0700673759f,-0.997542262f},
{0.056070447f,-0.998426795f},{0.0420624875f,-0.99911499f},{0.0280462559f,-0.999606609f},{0.0140245073f,-0.999901652f},
{6.12323426e-17f,-1.0f},{-0.0140245073f,-0.999901652f},{-0.0280462559f,-0.999606609f},{-0.0420624875f,-0.99911499f},
{-0.056070447f,-0.998426795f},{-0.0700673759f,-0.997542262f},{-0.0840505213f,-0.996461511f},{-0.0980171412f,-0.99518472f},
{-0.111964479f,-0.993712187f},{-0.125889793f,-0.99204421f},{-0.139790341f,-0.990181148f},{-0.153663397f,-0.988123238f},
{-0.167506218f,-0.985871017f},{-0.181316108f,-0.983424842f},{-0.195090324f,-0.980785251f},{-0.208826169f,-0.977952778f},
{-0.222520933f,-0.974927902f},{-0.236171931f,-0.971711278f},{-0.249776483f,-0.968303502f},{-0.26333189f,-0.964705288f},
{-0.276835501f,-0.960917294f},{-0.290284663f,-0.956940353f},{-0.303676754f,-0.952775121f},{-0.317009091f,-0.948422492f},
{-0.330279052f,-0.943883359f},{-0.343484074f,-0.939158499f},{-0.356621534f,-0.934248924f},{-0.369688839f,-0.929155588f},
{-0.382683426f,-0.923879504f},{-0.395602763f,-0.918421745f},{-0.408444256f,-0.912783265f},{-0.421205431f,-0.906965256f},
{-0.433883727f,-0.90096885f},{-0.446476698f,-0.894795239f},{-0.458981872f,-0.888445616f},{-0.471396744f,-0.881921291f},
{-0.483718902f,-0.875223398f},{-0.495945901f,-0.868353426f},{-0.508075356f,-0.861312628f},{-0.520104885f,-0.854102433f},
{-0.532032073f,-0.846724212f},{-0.543854654f,-0.839179456f},{-0.555570245f,-0.831469595f},{-0.567176521f,-0.823596239f},
{-0.578671277f,-0.815560877f},{-0.590052247f,-0.80736506f},{-0.601317108f,-0.799010456f},{-0.612463653f,-0.790498734f},
{-0.623489797f,-0.781831503f},{-0.634393275f,-0.773010433f},{-0.645172f,-0.764037371f},{-0.655823767f,-0.754913986f},
{-0.66634655f,-0.745642185f},{-0.676738322f,-0.736223638f},{-0.686996937f,-0.726660311f},{-0.697120428f,-0.716954052f},
{-0.707106769f,-0.707106769f},{-0.716954052f,-0.697120428f},{-0.726660311f,-0.686996937f},{-0.736223638f,-0.676738322f},
{-0.745642185f,-0.66634655f},{-0.754913986f,-0.655823767f},{-0.764037371f,-0.645172f},{-0.773010433f,-0.634393275f},
{-0.781831503f,-0.623489797f},{-0.790498734f,-0.612463653f},{-0.799010456f,-0.601317108f},{-0.80736506f,-0.590052247f},
{-0.815560877f,-0.578671277f},{-0.823596239f,-0.567176521f},{-0.831469595f,-0.555570245f},{-0.839179456f,-0.543854654f},
{-0.846724212f,-0.532032073f},{-0.854102433f,-0.520104885f},{-0.861312628f,-0.508075356f},{-0.868353426f,-0.495945901f},
{-0.875223398f,-0.483718902f},{-0.881921291f,-0.471396744f},{-0.888445616f,-0.458981872f},{-0.894795239f,-0.446476698f},
{-0.90096885f,-0.433883727f},{-0.906965256f,-0.421205431f},{-0.912783265f,-0.408444256f},{-0.918421745f,-0.395602763f},
{-0.923879504f,-0.382683426f},{-0.929155588f,-0.369688839f},{-0.934248924f,-0.356621534f},{-0.939158499f,-0.343484074f},
{-0.943883359f,-0.330279052f},{-0.948422492f,-0.317009091f},{-0.952775121f,-0.303676754f},{-0.956940353f,-0.290284663f},
{-0.960917294f,-0.276835501f},{-0.964705288f,-0.26333189f},{-0.968303502f,-0.249776483f},{-0.971711278f,-0.236171931f},
{-0.974927902f,-0.222520933f},{-0.977952778f,-0.208826169f},{-0.980785251f,-0.195090324f},{-0.983424842f,-0.181316108f},
{-0.985871017f,-0.167506218f},{-0.988123238f,-0.153663397f},{-0.990181148f,-0.139790341f},{-0.99204421f,-0.125889793f},
{-0.993712187f,-0.111964479f},{-0.99518472f,-0.0980171412f},{-0.996461511f,-0.0840505213f},{-0.997542262f,-0.0700673759f},
{-0.998426795f,-0.056070447f},{-0.99911499f,-0.0420624875f},{-0.999606609f,-0.0280462559f},{-0.999901652f,-0.0140245073f},
{-1.0f,-1.22464685e-16f},{-0.999901652f,0.0140245073f},{-0.999606609f,0.0280462559f},{-0.99911499f,0.0420624875f},
{-0.998426795f,0.056070447f},{-0.997542262f,0.0700673759f},{-0.996461511f,0.0840505213f},{-0.99518472f,0.0980171412f},
{-0.993712187f,0.111964479f},{-0.99204421f,0.125889793f},{-0.990181148f,0.139790341f},{-0.988123238f,0.153663397f},
{-0.985871017f,0.167506218f},{-0.983424842f,0.181316108f},{-0.980785251f,0.195090324f},{-0.977952778f,0.208826169f},
{-0.974927902f,0.222520933f},{-0.971711278f,0.236171931f},{-0.968303502f,0.249776483f},{-0.964705288f,0.26333189f},
{-0.960917294f,0.276835501f},{-0.956940353f,0.290284663f},{-0.952775121f,0.303676754f},{-0.948422492f,0.317009091f},
{-0.943883359f,0.330279052f},{-0.939158499f,0.343484074f},{-0.934248924f,0.356621534f},{-0.929155588f,0.369688839f},
{-0.923879504f,0.382683426f},{-0.918421745f,0.395602763f},{-0.912783265f,0.408444256f},{-0.906965256f,0.421205431f},
{-0.90096885f,0.433883727f},{-0.894795239f,0.446476698f},{-0.888445616f,0.458981872f},{-0.881921291f,0.471396744f},
{-0.875223398f,0.483718902f},{-0.868353426f,0.495945901f},{-0.861312628f,0.508075356f},{-0.854102433f,0.520104885f},
{-0.846724212f,0.532032073f},{-0.839179456f,0.543854654f},{-0.831469595f,0.555570245f},{-0.823596239f,0.567176521f},
{-0.815560877f,0.578671277f},{-0.80736506f,0.590052247f},{-0.799010456f,0.601317108f},{-0.790498734f,0.612463653f},
{-0.781831503f,0.623489797f},{-0.773010433f,0.634393275f},{-0.764037371f,0.645172f},{-0.754913986f,0.655823767f},
{-0.745642185f,0.66634655f},{-0.736223638f,0.676738322f},{-0.726660311f,0.686996937f},{-0.716954052f,0.697120428f},
{-0.707106769f,0.707106769f},{-0.697120428f,0.716954052f},{-0.686996937f,0.726660311f},{-0.676738322f,0.736223638f},
{-0.66634655f,0.745642185f},{-0.655823767f,0.754913986f},{-0.645172f,0.764037371f},{-0.634393275f,0.773010433f},
{-0.623489797f,0.781831503f},{-0.612463653f,0.790498734f},{-0.601317108f,0.799010456f},{-0.590052247f,0.80736506f},
{-0.578671277f,0.815560877f},{-0.567176521f,0.823596239f},{-0.555570245f,0.831469595f},{-0.543854654f,0.839179456f},
{-0.532032073f,0.846724212f},{-0.520104885f,0.854102433f},{-0.508075356f,0.861312628f},{-0.495945901f,0.868353426f},
{-0.483718902f,0.875223398f},{-0.471396744f,0.881921291f},{-0.458981872f,0.888445616f},{-0.446476698f,0.894795239f},
{-0.433883727f,0.90096885f},{-0.421205431f,0.906965256f},{-0.408444256f,0.912783265f},{-0.395602763f,0.918421745f},
{-0.382683426f,0.923879504f},{-0.369688839f,0.929155588f},{-0.356621534f,0.934248924f},{-0.343484074f,0.939158499f},
{-0.330279052f,0.943883359f},{-0.317009091f,0.948422492f},{-0.303676754f,0.952775121f},{-0.290284663f,0.956940353f},
{-0.276835501f,0.960917294f},{-0.26333189f,0.964705288f},{-0.249776483f,0.968303502f},{-0.236171931f,0.971711278f},
{-0.222520933f,0.974927902f},{-0.208826169f,0.977952778f},{-0.195090324f,0.980785251f},{-0.181316108f,0.983424842f},
{-0.167506218f,0.985871017f},{-0.153663397f,0.988123238f},{-0.139790341f,0.990181148f},{-0.125889793f,0.99204421f},
{-0.111964479f,0.993712187f},{-0.0980171412f,0.99518472f},{-0.0840505213f,0.996461511f},{-0.0700673759f,0.997542262f},
{-0.056070447f,0.998426795f},{-0.0420624875f,0.99911499f},{-0.0280462559f,0.999606609f},{-0.0140245073f,0.999901652f},
{-1.83697015e-16f,1.0f},{0.0140245073f,0.999901652f},{0.0280462559f,0.999606609f},{0.0420624875f,0.99911499f},
{0.056070447f,0.998426795f},{0.0700673759f,0.997542262f},{0.0840505213f,0.996461511f},{0.0980171412f,0.99518472f},
{0.111964479f,0.993712187f},{0.125889793f,0.99204421f},{0.139790341f,0.990181148f},{0.153663397f,0.988123238f},
{0.167506218f,0.985871017f},{0.181316108f,0.983424842f},{0.195090324f,0.980785251f},{0.208826169f,0.977952778f},
{0.222520933f,0.974927902f},{0.236171931f,0.971711278f},{0.249776483f,0.968303502f},{0.26333189f,0.964705288f},
{0.276835501f,0.960917294f},{0.290284663f,0.956940353f},{0.303676754f,0.952775121f},{0.317009091f,0.948422492f},
{0.330279052f,0.943883359f},{0.343484074f,0.939158499f},{0.356621534f,0.934248924f},{0.369688839f,0.929155588f},
{0.382683426f,0.923879504f},{0.395602763f,0.918421745f},{0.408444256f,0.912783265f},{0.421205431f,0.906965256f},
{0.433883727f,0.90096885f},{0.446476698f,0.894795239f},{0.458981872f,0.888445616f},{0.471396744f,0.881921291f},
{0.483718902f,0.875223398f},{0.495945901f,0.868353426f},{0.508075356f,0.861312628f},{0.520104885f,0.854102433f},
{0.532032073f,0.846724212f},{0.543854654f,0.839179456f},{0.555570245f,0.831469595f},{0.567176521f,0.823596239f},
{0.578671277f,0.815560877f},{0.590052247f,0.80736506f},{0.601317108f,0.799010456f},{0.612463653f,0.790498734f},
{0.623489797f,0.781831503f},{0.634393275f,0.773010433f},{0.645172f,0.764037371f},{0.655823767f,0.754913986f},
{0.66634655f,0.745642185f},{0.676738322f,0.736223638f},{0.686996937f,0.726660311f},{0.697120428f,0.716954052f},
{0.707106769f,0.707106769f},{0.716954052f,0.697120428f},{0.726660311f,0.686996937f},{0.736223638f,0.676738322f},
{0.745642185f,0.66634655f},{0.754913986f,0.655823767f},{0.764037371f,0.645172f},{0.773010433f,0.634393275f},
{0.781831503f,0.623489797f},{0.790498734f,0.612463653f},{0.799010456f,0.601317108f},{0.80736506f,0.590052247f},
{0.815560877f,0.578671277f},{0.823596239f,0.567176521f},{0.831469595f,0.555570245f},{0.839179456f,0.543854654f},
{0.846724212f,0.532032073f},{0.854102433f,0.520104885f},{0.861312628f,0.508075356f},{0.868353426f,0.495945901f},
{0.875223398f,0.483718902f},{0.881921291f,0.471396744f},{0.888445616f,0.458981872f},{0.894795239f,0.446476698f},
{0.90096885f,0.433883727f},{0.906965256f,0.421205431f},{0.912783265f,0.408444256f},{0.918421745f,0.395602763f},
{0.923879504f,0.382683426f},{0.929155588f,0.369688839f},{0.934248924f,0.356621534f},{0.939158499f,0.343484074f},
{0.943883359f,0.330279052f},{0.948422492f,0.317009091f},{0.952775121f,0.303676754f},{0.956940353f,0.290284663f},
{0.960917294f,0.276835501f},{0.964705288f,0.26333189f},{0.968303502f,0.249776483f},{0.971711278f,0.236171931f},
{0.974927902f,0.222520933f},{0.977952778f,0.208826169f},{0.980785251f,0.195090324f},{0.983424842f,0.181316108f},
{0.985871017f,0.167506218f},{0.988123238f,0.153663397f},{0.990181148f,0.139790341f},{0.99204421f,0.125889793f},
{0.993712187f,0.111964479f},{0.99518472f,0.0980171412f},{0.996461511f,0.0840505213f},{0.997542262f,0.0700673759f},
{0.998426795f,0.056070447f},{0.99911499f,0.0420624875f},{0.999606609f,0.0280462559f},{0.999901652f,0.0140245073f},
};

namespace {

typedef __nv_bfloat16 bf16;

constexpr int SEQ = 2048, DM = 448, NF = 225;
constexpr int KT = 128;
constexpr int NKT = SEQ / KT;
constexpr int KV_TILE_BYTES = 16384;

__device__ __align__(128) bf16 g_Q[SEQ * DM];
__device__ __align__(1024) unsigned char g_KV[NKT * KV_TILE_BYTES];
__device__ float g_kn[128];
__device__ __align__(128) bf16 g_O[SEQ * DM];
__device__ __align__(128) float2 g_X[NF * SEQ];
__device__ __align__(128) uint32_t g_W[NF * SEQ];

__device__ __forceinline__ uint32_t smem_u32(const void* p) {
    return (uint32_t)__cvta_generic_to_shared(p);
}
__device__ __forceinline__ void pdl_wait() { asm volatile("griddepcontrol.wait;\n" ::: "memory"); }
__device__ __forceinline__ void pdl_launch() { asm volatile("griddepcontrol.launch_dependents;\n" ::: "memory"); }
__device__ __forceinline__ void cp_async16(uint32_t dst, const void* src) {
    asm volatile("cp.async.cg.shared.global [%0], [%1], 16;\n" ::"r"(dst), "l"(src));
}
__device__ __forceinline__ void cp_async_commit() { asm volatile("cp.async.commit_group;\n"); }
template <int N>
__device__ __forceinline__ void cp_async_wait() { asm volatile("cp.async.wait_group %0;\n" ::"n"(N)); }

__device__ __forceinline__ uint32_t pack_bf16(float lo, float hi) {
    uint32_t r;
    asm("cvt.rn.bf16x2.f32 %0, %1, %2;\n" : "=r"(r) : "f"(hi), "f"(lo));
    return r;
}
__device__ __forceinline__ uint32_t pack_bf16_v(float lo, float hi) {
    uint32_t r;
    asm volatile("cvt.rn.bf16x2.f32 %0, %1, %2;\n" : "=r"(r) : "f"(hi), "f"(lo));
    return r;
}
__device__ __forceinline__ float bf16lo(uint32_t v) { return __uint_as_float(v << 16); }
__device__ __forceinline__ float bf16hi(uint32_t v) { return __uint_as_float(v & 0xffff0000u); }

__device__ __forceinline__ void wg_fence() { asm volatile("wgmma.fence.sync.aligned;\n" ::: "memory"); }
__device__ __forceinline__ void wg_commit() { asm volatile("wgmma.commit_group.sync.aligned;\n" ::: "memory"); }
template <int N>
__device__ __forceinline__ void wg_wait() { asm volatile("wgmma.wait_group.sync.aligned %0;\n" ::"n"(N) : "memory"); }

__device__ __forceinline__ uint64_t make_desc(uint32_t addr, uint32_t lbo, uint32_t sbo) {
    return (uint64_t)((addr & 0x3FFFF) >> 4) | ((uint64_t)(lbo >> 4) << 16) | ((uint64_t)(sbo >> 4) << 32);
}

__device__ __forceinline__ void mbar_init(uint32_t a, uint32_t cnt) {
    asm volatile("mbarrier.init.shared::cta.b64 [%0], %1;\n" ::"r"(a), "r"(cnt));
}
__device__ __forceinline__ void mbar_expect_tx(uint32_t a, uint32_t bytes) {
    asm volatile("mbarrier.arrive.expect_tx.shared::cta.b64 _, [%0], %1;\n" ::"r"(a), "r"(bytes) : "memory");
}
__device__ __forceinline__ void mbar_arrive(uint32_t a) {
    asm volatile("mbarrier.arrive.shared::cta.b64 _, [%0];\n" ::"r"(a) : "memory");
}
__device__ __forceinline__ void mbar_wait(uint32_t a, uint32_t parity) {
    asm volatile(
        "{\n"
        ".reg .pred P1;\n"
        "LAB_WAIT:\n"
        "mbarrier.try_wait.parity.shared::cta.b64 P1, [%0], %1;\n"
        "@P1 bra DONE;\n"
        "bra LAB_WAIT;\n"
        "DONE:\n"
        "}\n" ::"r"(a), "r"(parity) : "memory");
}
__device__ __forceinline__ void bulk_g2s(uint32_t dst, const void* src, uint32_t bytes, uint32_t mbar) {
    asm volatile("cp.async.bulk.shared::cluster.global.mbarrier::complete_tx::bytes [%0], [%1], %2, [%3];\n"
                 ::"r"(dst), "l"(src), "r"(bytes), "r"(mbar) : "memory");
}

__device__ __forceinline__ float2 cadd(float2 a, float2 b) { return make_float2(a.x + b.x, a.y + b.y); }
__device__ __forceinline__ float2 csub(float2 a, float2 b) { return make_float2(a.x - b.x, a.y - b.y); }
__device__ __forceinline__ float2 cmul(float2 a, float2 b) {
    return make_float2(fmaf(a.x, b.x, -a.y * b.y), fmaf(a.x, b.y, a.y * b.x));
}
__device__ __forceinline__ float2 cmulc(float2 a, float2 b) {
    return make_float2(fmaf(a.x, b.x, a.y * b.y), fmaf(a.y, b.x, -a.x * b.y));
}
template <bool INV> __device__ __forceinline__ float2 ctw(float2 a, float2 w) { return INV ? cmulc(a, w) : cmul(a, w); }
template <bool INV> __device__ __forceinline__ float2 rot90(float2 a) {
    return INV ? make_float2(-a.y, a.x) : make_float2(a.y, -a.x);
}

template <bool INV>
__device__ __forceinline__ void dft4(float2& a0, float2& a1, float2& a2, float2& a3) {
    float2 t0 = cadd(a0, a2), t1 = csub(a0, a2), t2 = cadd(a1, a3), t3 = rot90<INV>(csub(a1, a3));
    a0 = cadd(t0, t2); a2 = csub(t0, t2); a1 = cadd(t1, t3); a3 = csub(t1, t3);
}
template <bool INV>
__device__ __forceinline__ void dft8(float2 (&a)[8]) {
    dft4<INV>(a[0], a[2], a[4], a[6]);
    dft4<INV>(a[1], a[3], a[5], a[7]);
    const float h = 0.70710678118654752f;
    float2 o1 = a[3], o2 = a[5], o3 = a[7];
    if (!INV) {
        o1 = make_float2((o1.x + o1.y) * h, (o1.y - o1.x) * h);
        o2 = make_float2(o2.y, -o2.x);
        o3 = make_float2((o3.y - o3.x) * h, -(o3.x + o3.y) * h);
    } else {
        o1 = make_float2((o1.x - o1.y) * h, (o1.x + o1.y) * h);
        o2 = make_float2(-o2.y, o2.x);
        o3 = make_float2(-(o3.x + o3.y) * h, (o3.x - o3.y) * h);
    }
    float2 e0 = a[0], e1 = a[2], e2 = a[4], e3 = a[6], o0 = a[1];
    a[0] = cadd(e0, o0); a[4] = csub(e0, o0);
    a[1] = cadd(e1, o1); a[5] = csub(e1, o1);
    a[2] = cadd(e2, o2); a[6] = csub(e2, o2);
    a[3] = cadd(e3, o3); a[7] = csub(e3, o3);
}
template <bool INV>
__device__ __forceinline__ void dft16(float2 (&a)[16]) {
#pragma unroll
    for (int n2 = 0; n2 < 4; n2++) dft4<INV>(a[n2], a[4 + n2], a[8 + n2], a[12 + n2]);
    const float c1 = 0.92387953251128674f, s1 = 0.38268343236508977f, h = 0.70710678118654752f;
    const float2 w1 = make_float2(c1, -s1), w2 = make_float2(h, -h), w3 = make_float2(s1, -c1);
    const float2 w6 = make_float2(-h, -h), w9 = make_float2(-c1, s1);
    a[4 + 1] = ctw<INV>(a[4 + 1], w1); a[4 + 2] = ctw<INV>(a[4 + 2], w2); a[4 + 3] = ctw<INV>(a[4 + 3], w3);
    a[8 + 1] = ctw<INV>(a[8 + 1], w2); a[8 + 2] = rot90<INV>(a[8 + 2]);   a[8 + 3] = ctw<INV>(a[8 + 3], w6);
    a[12 + 1] = ctw<INV>(a[12 + 1], w3); a[12 + 2] = ctw<INV>(a[12 + 2], w6); a[12 + 3] = ctw<INV>(a[12 + 3], w9);
#pragma unroll
    for (int k1 = 0; k1 < 4; k1++) dft4<INV>(a[4 * k1], a[4 * k1 + 1], a[4 * k1 + 2], a[4 * k1 + 3]);
#pragma unroll
    for (int i = 0; i < 4; i++)
#pragma unroll
        for (int j = i + 1; j < 4; j++) { float2 tmp = a[4 * i + j]; a[4 * i + j] = a[4 * j + i]; a[4 * j + i] = tmp; }
}
template <bool INV>
__device__ __forceinline__ void dft7(float2 (&x)[7]) {
    const float C1 = 0.62348980185873353f, C2 = -0.22252093395631440f, C3 = -0.90096886790241913f;
    const float S1 = 0.78183148246802981f, S2 = 0.97492791218182361f, S3 = 0.43388373911755812f;
    float2 a1 = cadd(x[1], x[6]), a2 = cadd(x[2], x[5]), a3 = cadd(x[3], x[4]);
    float2 b1 = csub(x[1], x[6]), b2 = csub(x[2], x[5]), b3 = csub(x[3], x[4]);
    float2 x0 = x[0];
    float2 c1 = make_float2(x0.x + C1 * a1.x + C2 * a2.x + C3 * a3.x, x0.y + C1 * a1.y + C2 * a2.y + C3 * a3.y);
    float2 c2 = make_float2(x0.x + C2 * a1.x + C3 * a2.x + C1 * a3.x, x0.y + C2 * a1.y + C3 * a2.y + C1 * a3.y);
    float2 c3 = make_float2(x0.x + C3 * a1.x + C1 * a2.x + C2 * a3.x, x0.y + C3 * a1.y + C1 * a2.y + C2 * a3.y);
    float2 d1 = make_float2(S1 * b1.x + S2 * b2.x + S3 * b3.x, S1 * b1.y + S2 * b2.y + S3 * b3.y);
    float2 d2 = make_float2(S2 * b1.x - S3 * b2.x - S1 * b3.x, S2 * b1.y - S3 * b2.y - S1 * b3.y);
    float2 d3 = make_float2(S3 * b1.x - S1 * b2.x + S2 * b3.x, S3 * b1.y - S1 * b2.y + S2 * b3.y);
    x[0] = make_float2(x0.x + a1.x + a2.x + a3.x, x0.y + a1.y + a2.y + a3.y);
    d1 = rot90<INV>(d1); d2 = rot90<INV>(d2); d3 = rot90<INV>(d3);
    x[1] = cadd(c1, d1); x[6] = csub(c1, d1);
    x[2] = cadd(c2, d2); x[5] = csub(c2, d2);
    x[3] = cadd(c3, d3); x[4] = csub(c3, d3);
}

constexpr int RB = 7 * 72;
struct Tw448 { float2 a[6], b[7]; };
__device__ __forceinline__ void tw448_load(Tw448& w, int t) {
#pragma unroll
    for (int k1 = 1; k1 < 7; k1++) w.a[k1 - 1] = __ldg(&c_tw448[k1 * t]);
#pragma unroll
    for (int k2 = 1; k2 < 8; k2++) w.b[k2 - 1] = __ldg(&c_tw448[7 * k2 * (t & 7)]);
}
template <bool INV>
__device__ __forceinline__ void fft448(float2 (&v)[7], const Tw448& w, float2* buf, int t, int bar) {
    dft7<INV>(v);
#pragma unroll
    for (int k1 = 1; k1 < 7; k1++) v[k1] = ctw<INV>(v[k1], w.a[k1 - 1]);
#pragma unroll
    for (int k1 = 0; k1 < 7; k1++) buf[k1 * 72 + t] = v[k1];
    asm volatile("bar.sync %0, 64;\n" ::"r"(bar) : "memory");
    float2 u[8];
    const int k1 = t >> 3, n3 = t & 7;
    if (t < 56) {
#pragma unroll
        for (int n2 = 0; n2 < 8; n2++) u[n2] = buf[k1 * 72 + n2 * 8 + n3];
        dft8<INV>(u);
#pragma unroll
        for (int k2 = 1; k2 < 8; k2++) u[k2] = ctw<INV>(u[k2], w.b[k2 - 1]);
    }
    asm volatile("bar.sync %0, 64;\n" ::"r"(bar) : "memory");
    if (t < 56) {
#pragma unroll
        for (int k2 = 0; k2 < 8; k2++) buf[k1 * 72 + k2 * 9 + n3] = u[k2];
    }
    asm volatile("bar.sync %0, 64;\n" ::"r"(bar) : "memory");
    const int k2 = t & 7;
    if (t < 56) {
#pragma unroll
        for (int n = 0; n < 8; n++) u[n] = buf[k1 * 72 + k2 * 9 + n];
        dft8<INV>(u);
    }
    asm volatile("bar.sync %0, 64;\n" ::"r"(bar) : "memory");
    if (t < 56) {
#pragma unroll
        for (int k3 = 0; k3 < 8; k3++) buf[k1 + 7 * k2 + 56 * k3] = u[k3];
    }
}

constexpr int ROW_SMEM = NF * 18 * 8;
__device__ __forceinline__ void row_sync() { asm volatile("bar.sync 2, 512;\n" ::: "memory"); }

__device__ __forceinline__ void rows_fwd_role(unsigned char* sm, const bf16* __restrict__ x, int tid, int s0) {
    bf16 (*sx)[DM] = (bf16 (*)[DM])sm;
    float2 (*sb)[RB] = (float2 (*)[RB])sm;
    const uint32_t smu = smem_u32(sm);
#pragma unroll
    for (int i = 0; i < 2; i++) {
        const int idx = tid + i * 512;
        if (idx < 16 * 56) cp_async16(smu + idx * 16, (const unsigned char*)(x + (size_t)s0 * DM) + idx * 16);
    }
    cp_async_commit();
    Tw448 tw;
    tw448_load(tw, tid & 63);
    cp_async_wait<0>();
    row_sync();
    const int pr = tid >> 6, t = tid & 63;
    float2 v[7];
#pragma unroll
    for (int n1 = 0; n1 < 7; n1++)
        v[n1] = make_float2(__bfloat162float(sx[2 * pr][n1 * 64 + t]), __bfloat162float(sx[2 * pr + 1][n1 * 64 + t]));
    row_sync();
    fft448<false>(v, tw, sb[pr], t, pr + 3);
    row_sync();
    {
        const int p = tid & 7;
#pragma unroll
        for (int j = 0; j < 4; j++) {
            const int vv = (tid >> 3) + 64 * j;
            if (vv < NF) {
                const float2 z = sb[p][vv];
                const float2 zc = sb[p][vv == 0 ? 0 : DM - vv];
                *(float4*)&g_X[(size_t)vv * SEQ + s0 + 2 * p] = make_float4(z.x + zc.x, z.y - zc.y, z.y + zc.y, zc.x - z.x);
            }
        }
    }
}

__device__ __forceinline__ void rows_inv_role(unsigned char* sm, bf16* __restrict__ out, int tid, int s0) {
    float2* sy = (float2*)sm;
    float2 (*sb)[RB] = (float2 (*)[RB])sm;
    Tw448 tw;
    tw448_load(tw, tid & 63);
    pdl_wait();
    {
        float4 tmp[4];
#pragma unroll
        for (int i = 0; i < 4; i++) {
            const int idx = tid + i * 512;
            if (idx < NF * 8) tmp[i] = __ldcg((const float4*)(g_X + (size_t)(idx >> 3) * SEQ + s0) + (idx & 7));
        }
#pragma unroll
        for (int i = 0; i < 4; i++) {
            const int idx = tid + i * 512;
            if (idx < NF * 8) *(float4*)(sm + (idx >> 3) * 144 + (idx & 7) * 16) = tmp[i];
        }
    }
    row_sync();
    const int pr = tid >> 6, t = tid & 63;
    float2 v[7];
#pragma unroll
    for (int n1 = 0; n1 < 7; n1++) {
        const int k = n1 * 64 + t;
        const int kk = (k <= 224) ? k : DM - k;
        float4 ab = *(const float4*)&sy[kk * 18 + 2 * pr];
        float2 a = make_float2(ab.x, ab.y), b = make_float2(ab.z, ab.w);
        if (kk == 0 || kk == 224) { a.y = 0.f; b.y = 0.f; }
        if (k > 224) { a.y = -a.y; b.y = -b.y; }
        v[n1] = make_float2(a.x - b.y, a.y + b.x);
    }
    row_sync();
    fft448<true>(v, tw, sb[pr], t, pr + 3);
    row_sync();
    {
        const int r = tid >> 5, lane = tid & 31;
        bf16* orow = out + (size_t)(s0 + r) * 896 + 448;
#pragma unroll
        for (int j = 0; j < 7; j++) {
            const int c = 2 * (lane + 32 * j);
            const float4 z = *(const float4*)&sb[r >> 1][c];
            *(uint32_t*)(orow + c) = (r & 1) ? pack_bf16(z.y, z.w) : pack_bf16(z.x, z.z);
        }
    }
}

constexpr int GA_CHUNK = 128 * 128;
constexpr int GB_CHUNK = 64 * 128;
constexpr int GEMM_SMEM = 7 * (GA_CHUNK + GB_CHUNK) + ROW_SMEM + 1024;

__device__ __forceinline__ void tma_2d(uint32_t dst, const CUtensorMap* map, int c0, int c1, uint32_t mbar) {
    asm volatile("cp.async.bulk.tensor.2d.shared::cluster.global.mbarrier::complete_tx::bytes [%0], [%1, {%3, %4}], [%2];\n"
                 ::"r"(dst), "l"((uint64_t)map), "r"(mbar), "r"(c0), "r"(c1) : "memory");
}
__device__ __forceinline__ uint64_t make_desc_sw128(uint32_t addr) {
    return (uint64_t)((addr & 0x3FFFF) >> 4) | ((uint64_t)1 << 16) | ((uint64_t)(1024 >> 4) << 32) | ((uint64_t)1 << 62);
}
__device__ __forceinline__ void wgmma_ss_n64t(float (&d)[32], uint64_t da, uint64_t db) {
    asm volatile(
        "wgmma.mma_async.sync.aligned.m64n64k16.f32.bf16.bf16 "
        "{%0,%1,%2,%3,%4,%5,%6,%7,%8,%9,%10,%11,%12,%13,%14,%15,"
        "%16,%17,%18,%19,%20,%21,%22,%23,%24,%25,%26,%27,%28,%29,%30,%31},"
        "%32, %33, 1, 1, 1, 0, 1;\n"
        : "+f"(d[0]), "+f"(d[1]), "+f"(d[2]), "+f"(d[3]), "+f"(d[4]), "+f"(d[5]), "+f"(d[6]), "+f"(d[7]),
          "+f"(d[8]), "+f"(d[9]), "+f"(d[10]), "+f"(d[11]), "+f"(d[12]), "+f"(d[13]), "+f"(d[14]), "+f"(d[15]),
          "+f"(d[16]), "+f"(d[17]), "+f"(d[18]), "+f"(d[19]), "+f"(d[20]), "+f"(d[21]), "+f"(d[22]), "+f"(d[23]),
          "+f"(d[24]), "+f"(d[25]), "+f"(d[26]), "+f"(d[27]), "+f"(d[28]), "+f"(d[29]), "+f"(d[30]), "+f"(d[31])
        : "l"(da), "l"(db));
}

__device__ __forceinline__ void gemm_mainloop(float (&acc)[32], uint32_t sA, uint32_t sB, uint32_t bars, int wg) {
#pragma unroll
    for (int j = 0; j < 32; j++) acc[j] = 0.f;
#pragma unroll
    for (int j = 0; j < 32; j++) asm volatile("" : "+f"(acc[j])::"memory");
    const uint64_t dA = make_desc_sw128(sA + wg * 8192);
    const uint64_t dB = make_desc_sw128(sB);
#pragma unroll
    for (int c = 0; c < 7; c++) {
        mbar_wait(bars + c * 8, 0);
        wg_fence();
#pragma unroll
        for (int ks = 0; ks < 4; ks++)
            wgmma_ss_n64t(acc, dA + c * (GA_CHUNK >> 4) + ks * 2, dB + c * (GB_CHUNK >> 4) + ks * 128);
        wg_commit();
    }
    wg_wait<0>();
#pragma unroll
    for (int j = 0; j < 32; j++) asm volatile("" : "+f"(acc[j])::"memory");
}

__global__ void __launch_bounds__(768, 1)
qkv_kernel(const __grid_constant__ CUtensorMap mapX, const __grid_constant__ CUtensorMap mapW,
           const bf16* __restrict__ wk, const bf16* __restrict__ wv,
           const bf16* __restrict__ bx, const bf16* __restrict__ w_r, const bf16* __restrict__ w_i) {
    extern __shared__ unsigned char smem_raw[];
    __shared__ __align__(8) uint64_t s_bar[7];
    const int tid = (threadIdx.x < 512) ? threadIdx.x + 256 : threadIdx.x - 512, lane = tid & 31, warp = tid >> 5;
    const int mt = blockIdx.x >> 3, nt = blockIdx.x & 7;
    const int m0 = mt * 128, n0 = nt * 64;
    const uint32_t sA = (smem_u32(smem_raw) + 1023u) & ~1023u, sB = sA + 7 * GA_CHUNK;
    const uint32_t bars = smem_u32(&s_bar[0]);
    pdl_launch();
    if (warp >= 8) {
        rows_fwd_role(smem_raw + (sA - smem_u32(smem_raw)) + 7 * (GA_CHUNK + GB_CHUNK), bx, tid - 256, blockIdx.x * 16);
        return;
    }
    if (tid == 0) {
#pragma unroll
        for (int c = 0; c < 7; c++) mbar_init(bars + c * 8, 1);
        asm volatile("fence.mbarrier_init.release.cluster;\n" ::: "memory");
        asm volatile("fence.proxy.async.shared::cta;\n" ::: "memory");
#pragma unroll
        for (int c = 0; c < 7; c++) {
            mbar_expect_tx(bars + c * 8, nt < 7 ? GA_CHUNK + GB_CHUNK : GA_CHUNK);
            tma_2d(sA + c * GA_CHUNK, &mapX, c * 64, m0, bars + c * 8);
            if (nt < 7) tma_2d(sB + c * GB_CHUNK, &mapW, n0, c * 64, bars + c * 8);
        }
    }
    unsigned short wa[2][8], wb[2][8];
#pragma unroll
    for (int rr = 0; rr < 2; rr++) {
        const unsigned short* pr = (const unsigned short*)w_r + (size_t)(blockIdx.x * 16 + warp * 2 + rr) * NF + lane;
        const unsigned short* pi = (const unsigned short*)w_i + (size_t)(blockIdx.x * 16 + warp * 2 + rr) * NF + lane;
#pragma unroll
        for (int j = 0; j < 8; j++)
            if (j < 7 || lane == 0) {
                asm volatile("ld.global.nc.u16 %0, [%1];\n" : "=h"(wa[rr][j]) : "l"(pr + 32 * j));
                asm volatile("ld.global.nc.u16 %0, [%1];\n" : "=h"(wb[rr][j]) : "l"(pi + 32 * j));
            }
    }
    if (nt == 7) {
        unsigned char* sBp = smem_raw + (sB - smem_u32(smem_raw));
        const int u = tid & 15;
        const bf16* src = (u < 7) ? (wk + u * 4) : (wv + (u - 7) * 4);
#pragma unroll
        for (int hb = 0; hb < 2; hb++) {
            uint2 v[14];
#pragma unroll
            for (int i = 0; i < 14; i++) {
                const int k = (tid >> 4) + (hb * 14 + i) * 16;
                v[i] = (u < 14) ? __ldg((const uint2*)(src + (size_t)k * 28)) : make_uint2(0u, 0u);
            }
#pragma unroll
            for (int i = 0; i < 14; i++) {
                const int k = (tid >> 4) + (hb * 14 + i) * 16;
                *(uint2*)(sBp + k * 128 + (((u >> 1) ^ (k & 7)) << 4) + (u & 1) * 8) = v[i];
            }
        }
        asm volatile("fence.proxy.async.shared::cta;\n" ::: "memory");
    }
    asm volatile("bar.sync 1, 256;\n" ::: "memory");

    const int wg = warp >> 2;
    float acc[32];
    gemm_mainloop(acc, sA, sB, bars, wg);

    const int g = lane >> 2, t = lane & 3;
    const int r0 = m0 + warp * 16 + g, r1 = r0 + 8;
    if (nt < 7) {
        const float qs = 0.18898223650461362f * 1.4426950408889634f;
#pragma unroll
        for (int j = 0; j < 8; j++) {
            int col = n0 + j * 8 + 2 * t;
            *(uint32_t*)(g_Q + (size_t)r0 * DM + col) = pack_bf16(acc[4 * j] * qs, acc[4 * j + 1] * qs);
            *(uint32_t*)(g_Q + (size_t)r1 * DM + col) = pack_bf16(acc[4 * j + 2] * qs, acc[4 * j + 3] * qs);
        }
    } else {
        unsigned char* base0 = g_KV + (r0 >> 7) * KV_TILE_BYTES + ((r0 & 127) >> 3) * 512 + (r0 & 7) * 16;
        unsigned char* base1 = g_KV + (r1 >> 7) * KV_TILE_BYTES + ((r1 & 127) >> 3) * 512 + (r1 & 7) * 16;
        unsigned char* vbase0 = g_KV + (r0 >> 7) * KV_TILE_BYTES + ((r0 & 127) >> 3) * 512 + (r0 & 7) * 2;
        unsigned char* vbase1 = g_KV + (r1 >> 7) * KV_TILE_BYTES + ((r1 & 127) >> 3) * 512 + (r1 & 7) * 2;
        float n0s = 0.f, n1s = 0.f;
#pragma unroll
        for (int j = 0; j < 7; j++) {
            int c = j * 8 + 2 * t;
            uint32_t p0 = pack_bf16(acc[4 * j], acc[4 * j + 1]);
            uint32_t p1 = pack_bf16(acc[4 * j + 2], acc[4 * j + 3]);
            if (c < 28) {
                int off = (c >> 3) * 128 + (c & 7) * 2;
                *(uint32_t*)(base0 + off) = p0;
                *(uint32_t*)(base1 + off) = p1;
                float a = bf16lo(p0), b = bf16hi(p0);
                n0s += a * a + b * b;
                a = bf16lo(p1); b = bf16hi(p1);
                n1s += a * a + b * b;
            } else {
                int d = c - 28;
                int off = 8192 + (d >> 3) * 128 + (d & 7) * 16;
                *(unsigned short*)(vbase0 + off) = (unsigned short)(p0 & 0xffff);
                *(unsigned short*)(vbase0 + off + 16) = (unsigned short)(p0 >> 16);
                *(unsigned short*)(vbase1 + off) = (unsigned short)(p1 & 0xffff);
                *(unsigned short*)(vbase1 + off + 16) = (unsigned short)(p1 >> 16);
            }
        }
        if (t == 0) {
            uint2 pad = make_uint2(0x00003f80u, 0u);
            *(uint2*)(base0 + 3 * 128 + 8) = pad;
            *(uint2*)(base1 + 3 * 128 + 8) = pad;
        }
        {
            unsigned short pv = (t == 0) ? (unsigned short)0x3f80 : (unsigned short)0;
            *(unsigned short*)(vbase0 + 8192 + 3 * 128 + (4 + t) * 16) = pv;
            *(unsigned short*)(vbase1 + 8192 + 3 * 128 + (4 + t) * 16) = pv;
        }
        n0s += __shfl_xor_sync(0xffffffffu, n0s, 1);
        n0s += __shfl_xor_sync(0xffffffffu, n0s, 2);
        n1s += __shfl_xor_sync(0xffffffffu, n1s, 1);
        n1s += __shfl_xor_sync(0xffffffffu, n1s, 2);
        float m = fmaxf(n0s, n1s);
        m = fmaxf(m, __shfl_xor_sync(0xffffffffu, m, 4));
        m = fmaxf(m, __shfl_xor_sync(0xffffffffu, m, 8));
        m = fmaxf(m, __shfl_xor_sync(0xffffffffu, m, 16));
        if (lane == 0) g_kn[mt * 8 + warp] = m;
    }
    asm volatile("bar.sync 1, 256;\n" ::: "memory");
    uint32_t* st = (uint32_t*)(smem_raw + (sA - smem_u32(smem_raw)));
#pragma unroll
    for (int rr = 0; rr < 2; rr++)
#pragma unroll
        for (int j = 0; j < 8; j++)
            if (j < 7 || lane == 0) st[(warp * 2 + rr) * 227 + lane + 32 * j] = (uint32_t)wa[rr][j] | ((uint32_t)wb[rr][j] << 16);
    asm volatile("bar.sync 1, 256;\n" ::: "memory");
    {
        const int r = tid & 15;
#pragma unroll
        for (int j = 0; j < 15; j++) {
            const int vv = (tid >> 4) + 16 * j;
            if (vv < NF) g_W[(size_t)vv * SEQ + blockIdx.x * 16 + r] = st[r * 227 + vv];
        }
    }
}

__global__ void __launch_bounds__(768, 1)
outproj_kernel(const __grid_constant__ CUtensorMap mapO, const __grid_constant__ CUtensorMap mapW,
               bf16* __restrict__ out) {
    extern __shared__ unsigned char smem_raw[];
    __shared__ __align__(8) uint64_t s_bar[7];
    const int tid = (threadIdx.x < 512) ? threadIdx.x + 256 : threadIdx.x - 512, lane = tid & 31, warp = tid >> 5;
    const int mt = blockIdx.x >> 3, nt = blockIdx.x & 7;
    const int m0 = mt * 128, n0 = nt * 64;
    const uint32_t sA = (smem_u32(smem_raw) + 1023u) & ~1023u, sB = sA + 7 * GA_CHUNK;
    const uint32_t bars = smem_u32(&s_bar[0]);
    if (warp >= 8) {
        rows_inv_role(smem_raw + (sA - smem_u32(smem_raw)) + 7 * (GA_CHUNK + GB_CHUNK), out, tid - 256, blockIdx.x * 16);
        return;
    }
    if (nt >= 7) return;
    if (tid == 0) {
#pragma unroll
        for (int c = 0; c < 7; c++) mbar_init(bars + c * 8, 1);
        asm volatile("fence.mbarrier_init.release.cluster;\n" ::: "memory");
        asm volatile("fence.proxy.async.shared::cta;\n" ::: "memory");
#pragma unroll
        for (int c = 0; c < 7; c++) {
            mbar_expect_tx(bars + c * 8, GA_CHUNK + GB_CHUNK);
            tma_2d(sB + c * GB_CHUNK, &mapW, n0, c * 64, bars + c * 8);
        }
        pdl_wait();
#pragma unroll
        for (int c = 0; c < 7; c++) tma_2d(sA + c * GA_CHUNK, &mapO, c * 64, m0, bars + c * 8);
    }
    asm volatile("bar.sync 1, 256;\n" ::: "memory");
    float acc[32];
    gemm_mainloop(acc, sA, sB, bars, warp >> 2);
    const int g = lane >> 2, t = lane & 3;
    const int r0 = m0 + warp * 16 + g, r1 = r0 + 8;
#pragma unroll
    for (int j = 0; j < 8; j++) {
        int col = n0 + j * 8 + 2 * t;
        *(uint32_t*)(out + (size_t)r0 * 896 + col) = pack_bf16(acc[4 * j], acc[4 * j + 1]);
        *(uint32_t*)(out + (size_t)r1 * 896 + col) = pack_bf16(acc[4 * j + 2], acc[4 * j + 3]);
    }
}

__device__ __forceinline__ void aux_sync() { asm volatile("bar.sync 2, 128;\n" ::: "memory"); }

__device__ __forceinline__ void fft_col(int v, const float2* scol, const uint32_t* sw, const float2* tw, float2* buf, int tid) {
    float2* col = g_X + (size_t)v * SEQ;
    float2 a[16];
#pragma unroll
    for (int n1 = 0; n1 < 16; n1++) a[n1] = scol[n1 * 128 + tid];
    dft16<false>(a);
#pragma unroll
    for (int k1 = 1; k1 < 16; k1++) a[k1] = cmul(a[k1], tw[k1 * tid]);
    aux_sync();
#pragma unroll
    for (int k1 = 0; k1 < 16; k1++) buf[k1 * 136 + tid] = a[k1];
    aux_sync();
    const int k1 = tid >> 3, n3 = tid & 7;
#pragma unroll
    for (int n2 = 0; n2 < 16; n2++) a[n2] = buf[k1 * 136 + n2 * 8 + n3];
    dft16<false>(a);
#pragma unroll
    for (int k2 = 1; k2 < 16; k2++) a[k2] = cmul(a[k2], tw[16 * k2 * n3]);
    aux_sync();
#pragma unroll
    for (int k2 = 0; k2 < 16; k2++) buf[k2 * 144 + n3 * 18 + k1] = a[k2];
    aux_sync();
    const int j1 = tid & 15, j2 = tid >> 4;
#pragma unroll 1
    for (int h = 0; h < 2; h++) {
        float2 u[8];
#pragma unroll
        for (int n = 0; n < 8; n++) u[n] = buf[(j2 + 8 * h) * 144 + n * 18 + j1];
        dft8<false>(u);
#pragma unroll
        for (int k3 = 0; k3 < 8; k3++) {
            const float sc = 0.5f / (2048.0f * 448.0f);
            const uint32_t w = sw[tid + 128 * h + 256 * k3];
            u[k3] = cmul(u[k3], make_float2(bf16lo(w) * sc, bf16hi(w) * sc));
        }
        dft8<true>(u);
#pragma unroll
        for (int n = 1; n < 8; n++) u[n] = cmulc(u[n], tw[16 * (j2 + 8 * h) * n]);
#pragma unroll
        for (int n = 0; n < 8; n++) buf[(j2 + 8 * h) * 144 + n * 18 + j1] = u[n];
    }
    aux_sync();
#pragma unroll
    for (int k2 = 0; k2 < 16; k2++) a[k2] = buf[k2 * 144 + n3 * 18 + k1];
    dft16<true>(a);
#pragma unroll
    for (int n2 = 0; n2 < 16; n2++) a[n2] = cmulc(a[n2], tw[k1 * (n2 * 8 + n3)]);
    aux_sync();
#pragma unroll
    for (int n2 = 0; n2 < 16; n2++) buf[k1 * 136 + n2 * 8 + n3] = a[n2];
    aux_sync();
#pragma unroll
    for (int kk = 0; kk < 16; kk++) a[kk] = buf[kk * 136 + tid];
    dft16<true>(a);
#pragma unroll
    for (int n1 = 0; n1 < 16; n1++) col[n1 * 128 + tid] = a[n1];
}

constexpr int AUX_SMEM = 2304 * 8 + 2 * 16384 + 2 * 8192 + 16384;

__device__ __forceinline__ void aux_main(unsigned char* sm, int tid) {
    float2* buf = (float2*)sm;
    unsigned char* stg = sm + 2304 * 8;
    const uint32_t stgu = smem_u32(stg);
    const int v0 = blockIdx.x, v1 = blockIdx.x + gridDim.x;
    const bool two = v1 < NF;
    const float2* tw = (const float2*)(stg + 49152);
#pragma unroll
    for (int i = 0; i < 8; i++) cp_async16(stgu + 49152 + (tid + i * 128) * 16, (const unsigned char*)c_tw2048 + (tid + i * 128) * 16);
#pragma unroll
    for (int i = 0; i < 8; i++) cp_async16(stgu + (tid + i * 128) * 16, (const unsigned char*)(g_X + (size_t)v0 * SEQ) + (tid + i * 128) * 16);
#pragma unroll
    for (int i = 0; i < 4; i++) cp_async16(stgu + 32768 + (tid + i * 128) * 16, (const unsigned char*)(g_W + (size_t)v0 * SEQ) + (tid + i * 128) * 16);
    cp_async_commit();
    if (two) {
#pragma unroll
        for (int i = 0; i < 8; i++) cp_async16(stgu + 16384 + (tid + i * 128) * 16, (const unsigned char*)(g_X + (size_t)v1 * SEQ) + (tid + i * 128) * 16);
#pragma unroll
        for (int i = 0; i < 4; i++) cp_async16(stgu + 40960 + (tid + i * 128) * 16, (const unsigned char*)(g_W + (size_t)v1 * SEQ) + (tid + i * 128) * 16);
    }
    cp_async_commit();
#pragma unroll 1
    for (int c = 0; c < (two ? 2 : 1); c++) {
        if (c == 0) cp_async_wait<1>(); else cp_async_wait<0>();
        aux_sync();
        fft_col(c ? v1 : v0, (const float2*)(stg + c * 16384), (const uint32_t*)(stg + 32768 + c * 8192), tw, buf, tid);
    }
}

__device__ __forceinline__ void wgmma_n64(float (&d)[32], const uint32_t (&a)[4], uint32_t dlo, int scaleD) {
    asm volatile(
        "{\n.reg .pred p;\n.reg .b64 ds;\nsetp.ne.b32 p, %37, 0;\nmov.b64 ds, {%36, 32};\n"
        "wgmma.mma_async.sync.aligned.m64n64k16.f32.bf16.bf16 "
        "{%0,%1,%2,%3,%4,%5,%6,%7,%8,%9,%10,%11,%12,%13,%14,%15,"
        "%16,%17,%18,%19,%20,%21,%22,%23,%24,%25,%26,%27,%28,%29,%30,%31},"
        "{%32,%33,%34,%35}, ds, p, 1, 1, 0;\n}\n"
        : "+f"(d[0]), "+f"(d[1]), "+f"(d[2]), "+f"(d[3]), "+f"(d[4]), "+f"(d[5]), "+f"(d[6]), "+f"(d[7]),
          "+f"(d[8]), "+f"(d[9]), "+f"(d[10]), "+f"(d[11]), "+f"(d[12]), "+f"(d[13]), "+f"(d[14]), "+f"(d[15]),
          "+f"(d[16]), "+f"(d[17]), "+f"(d[18]), "+f"(d[19]), "+f"(d[20]), "+f"(d[21]), "+f"(d[22]), "+f"(d[23]),
          "+f"(d[24]), "+f"(d[25]), "+f"(d[26]), "+f"(d[27]), "+f"(d[28]), "+f"(d[29]), "+f"(d[30]), "+f"(d[31])
        : "r"(a[0]), "r"(a[1]), "r"(a[2]), "r"(a[3]), "r"(dlo), "r"(scaleD));
}
__device__ __forceinline__ void wgmma_n32t(float (&d)[16], uint32_t a0, uint32_t a1, uint32_t a2, uint32_t a3,
                                           uint32_t dlo) {
    asm volatile(
        "{\n.reg .b64 ds;\nmov.b64 ds, {%20, 8};\n"
        "wgmma.mma_async.sync.aligned.m64n32k16.f32.bf16.bf16 "
        "{%0,%1,%2,%3,%4,%5,%6,%7,%8,%9,%10,%11,%12,%13,%14,%15},"
        "{%16,%17,%18,%19}, ds, 1, 1, 1, 0;\n}\n"
        : "+f"(d[0]), "+f"(d[1]), "+f"(d[2]), "+f"(d[3]), "+f"(d[4]), "+f"(d[5]), "+f"(d[6]), "+f"(d[7]),
          "+f"(d[8]), "+f"(d[9]), "+f"(d[10]), "+f"(d[11]), "+f"(d[12]), "+f"(d[13]), "+f"(d[14]), "+f"(d[15])
        : "r"(a0), "r"(a1), "r"(a2), "r"(a3), "r"(dlo));
}

__device__ __forceinline__ float ex2_mufu(float x) {
    float y;
    asm("ex2.approx.ftz.f32 %0, %1;\n" : "=f"(y) : "f"(x));
    return y;
}
__device__ __forceinline__ float ex2_poly(float x) {
    float t = x + 12582912.f;
    float r = t - 12582912.f;
    float f = x - r;
    float p = fmaf(0.0551716685295105f, f, 0.2426111251115799f);
    p = fmaf(p, f, 0.6932609677314758f);
    p = fmaf(p, f, 0.9999280571937561f);
    return __int_as_float(__float_as_int(p) + (__float_as_int(t) << 23));
}

constexpr int AT_STAGES = 4;
constexpr int AT_THREADS = 640;
constexpr int AT_SMEM = AT_STAGES * KV_TILE_BYTES + AUX_SMEM + 1024;

#define POLY_MASK 0x0421

__device__ __forceinline__ void exp_inplace(float (&s)[32]) {
#pragma unroll
    for (int j = 0; j < 32; j++) s[j] = ((POLY_MASK >> (j & 15)) & 1) ? ex2_poly(s[j]) : ex2_mufu(s[j]);
}
__device__ __forceinline__ void pack_p(const float (&s)[32], uint32_t (&p)[16]) {
#pragma unroll
    for (int j = 0; j < 16; j++) p[j] = pack_bf16_v(s[2 * j], s[2 * j + 1]);
}
__device__ __forceinline__ void fence_regs(float (&s)[32]) {
#pragma unroll
    for (int j = 0; j < 32; j++) asm volatile("" : "+f"(s[j])::"memory");
}

__global__ void __launch_bounds__(AT_THREADS, 1)
attn_kernel() {
    extern __shared__ unsigned char smem_raw[];
    __shared__ __align__(8) uint64_t s_full[AT_STAGES], s_empty[AT_STAGES];
    const uint32_t sbase = (smem_u32(smem_raw) + 1023u) & ~1023u;
    const int tid = threadIdx.x, lane = tid & 31, warp = tid >> 5;
    const uint32_t full0 = smem_u32(&s_full[0]), empty0 = smem_u32(&s_empty[0]);
    if (tid == 0) {
#pragma unroll
        for (int i = 0; i < AT_STAGES; i++) {
            mbar_init(full0 + i * 8, 1);
            mbar_init(empty0 + i * 8, 4);
        }
        asm volatile("fence.mbarrier_init.release.cluster;\n" ::: "memory");
        asm volatile("fence.proxy.async.shared::cta;\n" ::: "memory");
    }
    pdl_wait();
    pdl_launch();
    if (tid == 0) {
#pragma unroll
        for (int i = 0; i < AT_STAGES; i++) {
            mbar_expect_tx(full0 + i * 8, KV_TILE_BYTES);
            bulk_g2s(sbase + i * KV_TILE_BYTES, g_KV + (size_t)i * KV_TILE_BYTES, KV_TILE_BYTES, full0 + i * 8);
        }
    }

    if (warp >= 16) {
        asm volatile("setmaxnreg.dec.sync.aligned.u32 64;\n");
        aux_main(smem_raw + (sbase - smem_u32(smem_raw)) + AT_STAGES * KV_TILE_BYTES, tid - 512);
        return;
    }
    asm volatile("setmaxnreg.inc.sync.aligned.u32 104;\n");

    const int g = lane >> 2, t = lane & 3;
    const int r0 = blockIdx.x * 256 + warp * 16 + g, r1 = r0 + 8;

    uint32_t qa[2][4];
    {
        const bf16* q0 = g_Q + (size_t)r0 * 28;
        const bf16* q1 = g_Q + (size_t)r1 * 28;
        qa[0][0] = *(const uint32_t*)(q0 + 2 * t);
        qa[0][1] = *(const uint32_t*)(q1 + 2 * t);
        qa[0][2] = *(const uint32_t*)(q0 + 8 + 2 * t);
        qa[0][3] = *(const uint32_t*)(q1 + 8 + 2 * t);
        qa[1][0] = *(const uint32_t*)(q0 + 16 + 2 * t);
        qa[1][1] = *(const uint32_t*)(q1 + 16 + 2 * t);
        qa[1][2] = (t < 2) ? *(const uint32_t*)(q0 + 24 + 2 * t) : 0u;
        qa[1][3] = (t < 2) ? *(const uint32_t*)(q1 + 24 + 2 * t) : 0u;
    }
    float km = fmaxf(fmaxf(g_kn[lane], g_kn[lane + 32]), fmaxf(g_kn[lane + 64], g_kn[lane + 96]));
#pragma unroll
    for (int o = 16; o > 0; o >>= 1) km = fmaxf(km, __shfl_xor_sync(0xffffffffu, km, o));
    float nq0 = 0.f, nq1 = 0.f;
#pragma unroll
    for (int ks = 0; ks < 2; ks++) {
        float a;
        a = bf16lo(qa[ks][0]); nq0 += a * a; a = bf16hi(qa[ks][0]); nq0 += a * a;
        a = bf16lo(qa[ks][2]); nq0 += a * a; a = bf16hi(qa[ks][2]); nq0 += a * a;
        a = bf16lo(qa[ks][1]); nq1 += a * a; a = bf16hi(qa[ks][1]); nq1 += a * a;
        a = bf16lo(qa[ks][3]); nq1 += a * a; a = bf16hi(qa[ks][3]); nq1 += a * a;
    }
    nq0 += __shfl_xor_sync(0xffffffffu, nq0, 1); nq0 += __shfl_xor_sync(0xffffffffu, nq0, 2);
    nq1 += __shfl_xor_sync(0xffffffffu, nq1, 1); nq1 += __shfl_xor_sync(0xffffffffu, nq1, 2);
    const float M0 = sqrtf(nq0 * km) * 1.01f, M1 = sqrtf(nq1 * km) * 1.01f;
    int unsafe;
    {
        const int ul = !(M0 <= 60.f) || !(M1 <= 60.f);
        asm volatile(
            "{\n.reg .pred p, q;\nsetp.ne.b32 p, %1, 0;\n"
            "barrier.cta.red.or.pred q, 1, 512, p;\n"
            "selp.b32 %0, 1, 0, q;\n}\n"
            : "=r"(unsafe) : "r"(ul) : "memory");
    }

    float o[16];
#pragma unroll
    for (int i = 0; i < 16; i++) o[i] = 0.f;
    uint32_t p[16];
    const uint32_t dK = (uint32_t)make_desc(sbase, 128, 512);
    const uint32_t dV = (uint32_t)make_desc(sbase + 8192, 512, 128);
    const bool releaser = (tid & 127) == 0;

    if (!unsafe) {
        if (t == 2) {
            qa[1][2] = (uint32_t)__bfloat16_as_ushort(__float2bfloat16_rn(-M0));
            qa[1][3] = (uint32_t)__bfloat16_as_ushort(__float2bfloat16_rn(-M1));
        }
        float s[32];
#pragma unroll
        for (int j = 0; j < 32; j++) s[j] = 0.f;
        fence_regs(s);
#pragma unroll
        for (int j = 0; j < 16; j++) asm volatile("" : "+f"(o[j])::"memory");
        mbar_wait(full0, 0);
        wg_fence();
        wgmma_n64(s, qa[0], dK, 0);
        wgmma_n64(s, qa[1], dK + 16, 1);
        wg_commit();
        wg_wait<0>();
        fence_regs(s);
        exp_inplace(s);
        pack_p(s, p);
#pragma unroll 1
        for (int it = 0; it < NKT / AT_STAGES; it++) {
#pragma unroll
            for (int st = 0; st < AT_STAGES; st++) {
                const int i = it * AT_STAGES + st;
                constexpr uint32_t TS = KV_TILE_BYTES >> 4;
                uint32_t dk = dK, dv = dV;
                asm volatile("" : "+r"(dk), "+r"(dv));
                wg_fence();
                wgmma_n64(s, qa[0], dk + st * TS + 256, 0);
                wgmma_n64(s, qa[1], dk + st * TS + 256 + 16, 1);
                wg_commit();
#pragma unroll
                for (int kk = 0; kk < 4; kk++)
                    wgmma_n32t(o, p[4 * kk], p[4 * kk + 1], p[4 * kk + 2], p[4 * kk + 3], dv + st * TS + kk * 64);
                wg_commit();
                wg_wait<1>();
                fence_regs(s);
                exp_inplace(s);
                wg_wait<0>();
                pack_p(s, p);
                if (st == AT_STAGES - 1 && it == NKT / AT_STAGES - 1) break;
                const int nst = (st + 1) % AT_STAGES;
                mbar_wait(full0 + nst * 8, (st == AT_STAGES - 1) ? ((it + 1) & 1) : (it & 1));
                asm volatile("" : "+r"(dk), "+r"(dv));
                wg_fence();
                wgmma_n64(s, qa[0], dk + nst * TS, 0);
                wgmma_n64(s, qa[1], dk + nst * TS + 16, 1);
                wg_commit();
#pragma unroll
                for (int kk = 0; kk < 4; kk++)
                    wgmma_n32t(o, p[4 * kk], p[4 * kk + 1], p[4 * kk + 2], p[4 * kk + 3], dv + st * TS + 256 + kk * 64);
                wg_commit();
                wg_wait<1>();
                fence_regs(s);
                exp_inplace(s);
                wg_wait<0>();
                pack_p(s, p);
                if (releaser) mbar_arrive(empty0 + st * 8);
                if (tid == 384 && i >= 1 && i - 1 + AT_STAGES < NKT) {
                    const int rs = (st + AT_STAGES - 1) % AT_STAGES;
                    mbar_wait(empty0 + rs * 8, ((i - 1) / AT_STAGES) & 1);
                    mbar_expect_tx(full0 + rs * 8, KV_TILE_BYTES);
                    bulk_g2s(sbase + rs * KV_TILE_BYTES, g_KV + (size_t)(i - 1 + AT_STAGES) * KV_TILE_BYTES,
                             KV_TILE_BYTES, full0 + rs * 8);
                }
            }
        }
        {
            constexpr uint32_t so = (AT_STAGES - 1) * (KV_TILE_BYTES >> 4) + 256;
            wg_fence();
#pragma unroll
            for (int kk = 0; kk < 4; kk++)
                wgmma_n32t(o, p[4 * kk], p[4 * kk + 1], p[4 * kk + 2], p[4 * kk + 3], dV + so + kk * 64);
            wg_commit();
        }
    } else {
        float s[32];
        float m0 = -INFINITY, m1 = -INFINITY;
#pragma unroll 1
        for (int i = 0; i < NKT; i++) {
            const int st = i % AT_STAGES;
            const uint32_t so = (uint32_t)(st * (KV_TILE_BYTES >> 4));
            mbar_wait(full0 + st * 8, (i / AT_STAGES) & 1);
#pragma unroll 1
            for (int hf = 0; hf < 2; hf++) {
                wg_fence();
                wgmma_n64(s, qa[0], dK + so + hf * 256, 0);
                wgmma_n64(s, qa[1], dK + so + hf * 256 + 16, 1);
                wg_commit();
                wg_wait<0>();
                fence_regs(s);
#pragma unroll
                for (int j = 0; j < 16; j++) asm volatile("" : "+f"(o[j])::"memory");
                if (hf == 0 && i > 0) {
                    if (releaser) mbar_arrive(empty0 + ((i - 1) % AT_STAGES) * 8);
                    if (tid == 384 && i >= 2 && i - 2 + AT_STAGES < NKT) {
                        const int rs = (i - 2) % AT_STAGES;
                        mbar_wait(empty0 + rs * 8, ((i - 2) / AT_STAGES) & 1);
                        mbar_expect_tx(full0 + rs * 8, KV_TILE_BYTES);
                        bulk_g2s(sbase + rs * KV_TILE_BYTES, g_KV + (size_t)(i - 2 + AT_STAGES) * KV_TILE_BYTES,
                                 KV_TILE_BYTES, full0 + rs * 8);
                    }
                }
                float x0 = m0, x1 = m1;
#pragma unroll
                for (int j = 0; j < 8; j++) {
                    x0 = fmaxf(x0, fmaxf(s[4 * j], s[4 * j + 1]));
                    x1 = fmaxf(x1, fmaxf(s[4 * j + 2], s[4 * j + 3]));
                }
                x0 = fmaxf(x0, __shfl_xor_sync(0xffffffffu, x0, 1)); x0 = fmaxf(x0, __shfl_xor_sync(0xffffffffu, x0, 2));
                x1 = fmaxf(x1, __shfl_xor_sync(0xffffffffu, x1, 1)); x1 = fmaxf(x1, __shfl_xor_sync(0xffffffffu, x1, 2));
                const float al0 = ex2_mufu(m0 - x0), al1 = ex2_mufu(m1 - x1);
                m0 = x0; m1 = x1;
#pragma unroll
                for (int j = 0; j < 4; j++) {
                    o[4 * j] *= al0; o[4 * j + 1] *= al0; o[4 * j + 2] *= al1; o[4 * j + 3] *= al1;
                }
#pragma unroll
                for (int j = 0; j < 8; j++) {
                    p[2 * j] = pack_bf16(ex2_mufu(s[4 * j] - m0), ex2_mufu(s[4 * j + 1] - m0));
                    p[2 * j + 1] = pack_bf16(ex2_mufu(s[4 * j + 2] - m1), ex2_mufu(s[4 * j + 3] - m1));
                }
                wg_fence();
#pragma unroll
                for (int kk = 0; kk < 4; kk++)
                    wgmma_n32t(o, p[4 * kk], p[4 * kk + 1], p[4 * kk + 2], p[4 * kk + 3], dV + so + hf * 256 + kk * 64);
                wg_commit();
            }
        }
    }
    wg_wait<0>();
#pragma unroll
    for (int j = 0; j < 16; j++) asm volatile("" : "+f"(o[j])::"memory");

    const float l0 = __shfl_sync(0xffffffffu, o[12], (lane & 28) | 2);
    const float l1 = __shfl_sync(0xffffffffu, o[14], (lane & 28) | 2);
    const float i0 = 1.f / l0, i1 = 1.f / l1;
    bf16* o0 = g_O + (size_t)r0 * 28;
    bf16* o1 = g_O + (size_t)r1 * 28;
#pragma unroll
    for (int j = 0; j < 4; j++) {
        if (j < 3 || t < 2) {
            *(uint32_t*)(o0 + j * 8 + 2 * t) = pack_bf16(o[4 * j] * i0, o[4 * j + 1] * i0);
            *(uint32_t*)(o1 + j * 8 + 2 * t) = pack_bf16(o[4 * j + 2] * i1, o[4 * j + 3] * i1);
        }
    }
}

}

extern "C" void kernel_launch(void* const* d_in, const int* in_sizes, int n_in, void* d_out, int out_size) {
    const bf16* A_x = (const bf16*)d_in[0];
    const bf16* A_wq = (const bf16*)d_in[1];
    const bf16* A_wk = (const bf16*)d_in[2];
    const bf16* A_wv = (const bf16*)d_in[3];
    const bf16* A_wo = (const bf16*)d_in[4];
    const bf16* B_x = (const bf16*)d_in[5];
    const bf16* B_wr = (const bf16*)d_in[6];
    const bf16* B_wi = (const bf16*)d_in[7];
    bf16* out = (bf16*)d_out;

    typedef CUresult (*EncodeFn)(CUtensorMap*, CUtensorMapDataType, cuuint32_t, void*, const cuuint64_t*,
                                 const cuuint64_t*, const cuuint32_t*, const cuuint32_t*, CUtensorMapInterleave,
                                 CUtensorMapSwizzle, CUtensorMapL2promotion, CUtensorMapFloatOOBfill);
    static bool init = false;
    static EncodeFn encode = nullptr;
    static void* pO = nullptr;
    if (!init) {
        cudaFuncSetAttribute(qkv_kernel, cudaFuncAttributeMaxDynamicSharedMemorySize, GEMM_SMEM);
        cudaFuncSetAttribute(outproj_kernel, cudaFuncAttributeMaxDynamicSharedMemorySize, GEMM_SMEM);
        cudaFuncSetAttribute(attn_kernel, cudaFuncAttributeMaxDynamicSharedMemorySize, AT_SMEM);
        cudaFuncSetAttribute(qkv_kernel, cudaFuncAttributePreferredSharedMemoryCarveout, 100);
        cudaFuncSetAttribute(outproj_kernel, cudaFuncAttributePreferredSharedMemoryCarveout, 100);
        cudaFuncSetAttribute(attn_kernel, cudaFuncAttributePreferredSharedMemoryCarveout, 100);
        cudaDriverEntryPointQueryResult qr;
        void* fn = nullptr;
        cudaGetDriverEntryPoint("cuTensorMapEncodeTiled", &fn, cudaEnableDefault, &qr);
        encode = (EncodeFn)fn;
        cudaGetSymbolAddress(&pO, g_O);
        init = true;
    }
    auto mk = [&](CUtensorMap* m, const void* p, int rows, int boxRows) {
        cuuint64_t dims[2] = {448, (cuuint64_t)rows};
        cuuint64_t strides[1] = {896};
        cuuint32_t box[2] = {64, (cuuint32_t)boxRows};
        cuuint32_t es[2] = {1, 1};
        encode(m, CU_TENSOR_MAP_DATA_TYPE_BFLOAT16, 2, (void*)p, dims, strides, box, es, CU_TENSOR_MAP_INTERLEAVE_NONE,
               CU_TENSOR_MAP_SWIZZLE_128B, CU_TENSOR_MAP_L2_PROMOTION_L2_128B, CU_TENSOR_MAP_FLOAT_OOB_FILL_NONE);
    };
    CUtensorMap mX, mWq, mO, mWo;
    mk(&mX, A_x, SEQ, 128);
    mk(&mWq, A_wq, 448, 64);
    mk(&mO, pO, SEQ, 128);
    mk(&mWo, A_wo, 448, 64);
    cudaStream_t s1 = cudaStreamPerThread;
    qkv_kernel<<<128, 768, GEMM_SMEM, s1>>>(mX, mWq, A_wk, A_wv, B_x, B_wr, B_wi);
    cudaLaunchAttribute at[1];
    at[0].id = cudaLaunchAttributeProgrammaticStreamSerialization;
    at[0].val.programmaticStreamSerializationAllowed = 1;
    cudaLaunchConfig_t cfg = {};
    cfg.gridDim = dim3(128); cfg.blockDim = dim3(AT_THREADS); cfg.dynamicSmemBytes = AT_SMEM; cfg.stream = s1;
    cfg.attrs = at; cfg.numAttrs = 1;
    cudaLaunchKernelEx(&cfg, attn_kernel);
    cfg.blockDim = dim3(768); cfg.dynamicSmemBytes = GEMM_SMEM;
    cudaLaunchKernelEx(&cfg, outproj_kernel, mO, mWo, out);
}
```
